```python
import torch

def _softmax(x, axis=-1):
    return torch.softmax(x, dim=axis)
def _gelu(x):
    return torch.nn.functional.gelu(x, approximate="tanh")
def _silu(x):
    return torch.nn.functional.silu(x)
def _sigmoid(x):
    return torch.sigmoid(x)
def _layernorm(x, axis=-1, eps=1e-5):
    m = x.mean(dim=axis, keepdim=True)
    v = x.var(dim=axis, keepdim=True, unbiased=False)
    return (x - m) / torch.sqrt(v + eps)
def _scatter_add(tgt, idx, src, axis=0):
    return tgt.clone().index_add_(axis, idx, src)
def _segment_sum(src, seg, n):
    out = torch.zeros((n,) + src.shape[1:], dtype=src.dtype)
    return out.index_add_(0, seg, src)
def _pad(x, pw):
    flat = tuple(v for pair in reversed(pw) for v in pair)
    return torch.nn.functional.pad(x, flat)

kernel_name = 'standalone__self_sup_conv_stem_wavlm__speech'

def setup_inputs():

    _w = (lambda a: (lambda t: t.to(torch.bfloat16) if t.is_floating_point() else t)(torch.as_tensor(a)))
    B, T, D, K = 2, 16000, 256, 3
    scale = (K * D) ** -0.5
    return {
        "x": _w((lambda *s: torch.randn(*s, dtype=torch.bfloat16) * 0.05)(B, T, D)),
        "w": _w((lambda *s: torch.randn(*s, dtype=torch.bfloat16) * 0.05)(K, D, D) * scale),
        "gn_gamma": _w((lambda *s: torch.randn(*s, dtype=torch.bfloat16) * 0.05)(D) * 0.1 + 1.0),
        "gn_beta": _w((lambda *s: torch.randn(*s, dtype=torch.bfloat16) * 0.05)(D) * 0.1),
    }

def reference(x, w, gn_gamma, gn_beta):
    B, T, D = x.shape
    K = w.shape[0]
    s = 2
    L = (T - K) // s + 1
    h = torch.einsum('blc,cd->bld', x[:, 0:s * L:s, :], w[0])
    for i in range(1, K):
        h = h + torch.einsum('blc,cd->bld', x[:, i:i + s * L:s, :], w[i])
    mu = torch.einsum('bld->bd', h)[:, None, :] / L
    var = torch.einsum('bld->bd', (h - mu) ** 2)[:, None, :] / L
    h = (h - mu) / torch.sqrt(var + 1e-5)
    h = h * gn_gamma[None, None, :] + gn_beta[None, None, :]
    return _gelu(h)
```

```cpp
#include <cuda_runtime.h>
#include <cuda_bf16.h>
#include <cuda.h>
#include <stdint.h>

namespace {

constexpr int B_ = 2, T_ = 16000, D_ = 256, L_ = 7999;
constexpr int NT = 248;
constexpr int TILES = 33;
constexpr int NREG = NT / 2;
constexpr int NCTA = B_ * TILES * 2;
constexpr int NTHREADS = 384;

constexpr int X_BYTES = 256 * 128;
constexpr int W_BYTES = 2 * 64 * 128;
constexpr int SET_BYTES = 2 * X_BYTES + 3 * W_BYTES;
constexpr int OFF_E = 0, OFF_O = X_BYTES, OFF_W = 2 * X_BYTES;
constexpr int OFF_BAR = 2 * SET_BYTES;
constexpr int SMEM_BYTES = OFF_BAR + 256 + 1024;

__device__ unsigned long long g_part[4 * TILES * 128];
#define STAMP(i)
#define STAMP_FLUSH(base)

__device__ __forceinline__ uint32_t smem_u32(const void* p) { return (uint32_t)__cvta_generic_to_shared(p); }
__device__ __forceinline__ void mbar_init(uint32_t bar, uint32_t cnt) {
  asm volatile("mbarrier.init.shared::cta.b64 [%0], %1;" ::"r"(bar), "r"(cnt) : "memory");
}
__device__ __forceinline__ void mbar_expect_tx(uint32_t bar, uint32_t bytes) {
  asm volatile("mbarrier.arrive.expect_tx.shared::cta.b64 _, [%0], %1;" ::"r"(bar), "r"(bytes) : "memory");
}
__device__ __forceinline__ bool mbar_try(uint32_t bar, uint32_t parity) {
  uint32_t ok;
  asm volatile("{\n.reg .pred p;\nmbarrier.try_wait.parity.shared::cta.b64 p, [%1], %2;\nselp.u32 %0, 1, 0, p;\n}"
               : "=r"(ok) : "r"(bar), "r"(parity) : "memory");
  return ok;
}
__device__ __forceinline__ bool mbar_try_cl(uint32_t bar, uint32_t parity) {
  uint32_t ok;
  asm volatile("{\n.reg .pred p;\nmbarrier.try_wait.parity.acquire.cluster.shared::cta.b64 p, [%1], %2;\nselp.u32 %0, 1, 0, p;\n}"
               : "=r"(ok) : "r"(bar), "r"(parity) : "memory");
  return ok;
}
constexpr long long WAIT_LIMIT = 100000000ll;
__device__ __forceinline__ void mbar_wait(uint32_t bar, uint32_t parity) {
  if (mbar_try(bar, parity)) return;
  const long long t0 = clock64();
  while (!mbar_try(bar, parity)) if (clock64() - t0 > WAIT_LIMIT) return;
}
__device__ __forceinline__ void mbar_wait_cl(uint32_t bar, uint32_t parity) {
  if (mbar_try_cl(bar, parity)) return;
  const long long t0 = clock64();
  while (!mbar_try_cl(bar, parity)) if (clock64() - t0 > WAIT_LIMIT) return;
}
__device__ __forceinline__ void mbar_arrive_local(uint32_t bar) {
  asm volatile("mbarrier.arrive.shared::cta.b64 _, [%0];" ::"r"(bar) : "memory");
}
__device__ __forceinline__ void mbar_arrive_cluster(uint32_t bar, uint32_t cta) {
  asm volatile("{\n.reg .b32 r;\nmapa.shared::cluster.u32 r, %0, %1;\n"
               "mbarrier.arrive.shared::cluster.b64 _, [r];\n}" ::"r"(bar), "r"(cta) : "memory");
}
__device__ __forceinline__ void tma_x(uint32_t dst, const CUtensorMap* m, uint32_t bar, int c, int par, int l, int b) {
  asm volatile("cp.async.bulk.tensor.4d.shared::cluster.global.mbarrier::complete_tx::bytes.multicast::cluster "
               "[%0], [%1, {%3, %4, %5, %6}], [%2], %7;"
               ::"r"(dst), "l"(m), "r"(bar), "r"(c), "r"(par), "r"(l), "r"(b), "h"((uint16_t)3) : "memory");
}
__device__ __forceinline__ void tma_x_prefetch(const CUtensorMap* m, int c, int par, int l, int b) {
  asm volatile("cp.async.bulk.prefetch.tensor.4d.L2.global [%0, {%1, %2, %3, %4}];"
               ::"l"(m), "r"(c), "r"(par), "r"(l), "r"(b) : "memory");
}
__device__ __forceinline__ void tma_w(uint32_t dst, const CUtensorMap* m, uint32_t bar, int d, int row) {
  asm volatile("cp.async.bulk.tensor.2d.shared::cluster.global.mbarrier::complete_tx::bytes "
               "[%0], [%1, {%3, %4}], [%2];"
               ::"r"(dst), "l"(m), "r"(bar), "r"(d), "r"(row) : "memory");
}
__device__ __forceinline__ void tma_store(const CUtensorMap* m, uint32_t src, int d, int l, int b) {
  asm volatile("cp.async.bulk.tensor.3d.global.shared::cta.bulk_group [%0, {%2, %3, %4}], [%1];"
               ::"l"(m), "r"(src), "r"(d), "r"(l), "r"(b) : "memory");
}
__device__ __forceinline__ uint64_t make_desc(uint32_t addr) {
  return (uint64_t)((addr & 0x3FFFF) >> 4) | ((uint64_t)1 << 16) | ((uint64_t)64 << 32) | ((uint64_t)1 << 62);
}
__device__ __forceinline__ void wg_fence() { asm volatile("wgmma.fence.sync.aligned;" ::: "memory"); }
__device__ __forceinline__ void wg_commit() { asm volatile("wgmma.commit_group.sync.aligned;" ::: "memory"); }
template <int N> __device__ __forceinline__ void wg_wait() { asm volatile("wgmma.wait_group.sync.aligned %0;" ::"n"(N) : "memory"); }
__device__ __forceinline__ float tanh_fast(float x) { float y; asm("tanh.approx.f32 %0, %1;" : "=f"(y) : "f"(x)); return y; }
__device__ __forceinline__ uint32_t pack_bf16(float lo, float hi) {
  uint32_t r; asm("cvt.rn.bf16x2.f32 %0, %1, %2;" : "=r"(r) : "f"(hi), "f"(lo)); return r;
}
__device__ __forceinline__ float gelu_half(float hh) {
  const float c1 = 2.0f * 0.7978845608028654f, c3 = 8.0f * 0.7978845608028654f * 0.044715f;
  float u = hh * fmaf(hh * hh, c3, c1);
  return fmaf(hh, tanh_fast(u), hh);
}

#define PREFETCH 0
#define XPROMO CU_TENSOR_MAP_L2_PROMOTION_L2_128B

#define CWAIT(a, b) mbar_wait(a, b)
#define MMA(a, b, c, d) wgmma_n248(a, b, c, d)

#define EARLY_PF 0
#define DELAY1 1
#define RELAXED_ARRIVE 1
#define STAG 6
#define POLL_SLEEP 0
#define SENTINEL 1
#define SENT_CH 0
#define PF_N 0
#define PF_W 1
__device__ __forceinline__ void wgmma_n248(float (&d)[124], uint64_t da, uint64_t db, int scale_d) {
  asm volatile("{\n.reg .pred p;\nsetp.ne.b32 p, %126, 0;\n"
    "wgmma.mma_async.sync.aligned.m64n248k16.f32.bf16.bf16 "
    "{%0, %1, %2, %3, %4, %5, %6, %7, %8, %9, %10, %11, %12, %13, %14, %15, "
    "%16, %17, %18, %19, %20, %21, %22, %23, %24, %25, %26, %27, %28, %29, %30, %31, "
    "%32, %33, %34, %35, %36, %37, %38, %39, %40, %41, %42, %43, %44, %45, %46, %47, "
    "%48, %49, %50, %51, %52, %53, %54, %55, %56, %57, %58, %59, %60, %61, %62, %63, "
    "%64, %65, %66, %67, %68, %69, %70, %71, %72, %73, %74, %75, %76, %77, %78, %79, "
    "%80, %81, %82, %83, %84, %85, %86, %87, %88, %89, %90, %91, %92, %93, %94, %95, "
    "%96, %97, %98, %99, %100, %101, %102, %103, %104, %105, %106, %107, %108, %109, %110, %111, "
    "%112, %113, %114, %115, %116, %117, %118, %119, %120, %121, %122, %123}, "
    "%124, %125, p, 1, 1, 1, 0;\n}\n"
    : "+f"(d[0]), "+f"(d[1]), "+f"(d[2]), "+f"(d[3]), "+f"(d[4]), "+f"(d[5]), "+f"(d[6]), "+f"(d[7]),
      "+f"(d[8]), "+f"(d[9]), "+f"(d[10]), "+f"(d[11]), "+f"(d[12]), "+f"(d[13]), "+f"(d[14]), "+f"(d[15]),
      "+f"(d[16]), "+f"(d[17]), "+f"(d[18]), "+f"(d[19]), "+f"(d[20]), "+f"(d[21]), "+f"(d[22]), "+f"(d[23]),
      "+f"(d[24]), "+f"(d[25]), "+f"(d[26]), "+f"(d[27]), "+f"(d[28]), "+f"(d[29]), "+f"(d[30]), "+f"(d[31]),
      "+f"(d[32]), "+f"(d[33]), "+f"(d[34]), "+f"(d[35]), "+f"(d[36]), "+f"(d[37]), "+f"(d[38]), "+f"(d[39]),
      "+f"(d[40]), "+f"(d[41]), "+f"(d[42]), "+f"(d[43]), "+f"(d[44]), "+f"(d[45]), "+f"(d[46]), "+f"(d[47]),
      "+f"(d[48]), "+f"(d[49]), "+f"(d[50]), "+f"(d[51]), "+f"(d[52]), "+f"(d[53]), "+f"(d[54]), "+f"(d[55]),
      "+f"(d[56]), "+f"(d[57]), "+f"(d[58]), "+f"(d[59]), "+f"(d[60]), "+f"(d[61]), "+f"(d[62]), "+f"(d[63]),
      "+f"(d[64]), "+f"(d[65]), "+f"(d[66]), "+f"(d[67]), "+f"(d[68]), "+f"(d[69]), "+f"(d[70]), "+f"(d[71]),
      "+f"(d[72]), "+f"(d[73]), "+f"(d[74]), "+f"(d[75]), "+f"(d[76]), "+f"(d[77]), "+f"(d[78]), "+f"(d[79]),
      "+f"(d[80]), "+f"(d[81]), "+f"(d[82]), "+f"(d[83]), "+f"(d[84]), "+f"(d[85]), "+f"(d[86]), "+f"(d[87]),
      "+f"(d[88]), "+f"(d[89]), "+f"(d[90]), "+f"(d[91]), "+f"(d[92]), "+f"(d[93]), "+f"(d[94]), "+f"(d[95]),
      "+f"(d[96]), "+f"(d[97]), "+f"(d[98]), "+f"(d[99]), "+f"(d[100]), "+f"(d[101]), "+f"(d[102]), "+f"(d[103]),
      "+f"(d[104]), "+f"(d[105]), "+f"(d[106]), "+f"(d[107]), "+f"(d[108]), "+f"(d[109]), "+f"(d[110]), "+f"(d[111]),
      "+f"(d[112]), "+f"(d[113]), "+f"(d[114]), "+f"(d[115]), "+f"(d[116]), "+f"(d[117]), "+f"(d[118]), "+f"(d[119]),
      "+f"(d[120]), "+f"(d[121]), "+f"(d[122]), "+f"(d[123])
    : "l"(da), "l"(db), "r"(scale_d));
}

__global__ void __launch_bounds__(NTHREADS, 1)
conv_stem_kernel(const __grid_constant__ CUtensorMap mx, const __grid_constant__ CUtensorMap mw,
                 const __grid_constant__ CUtensorMap mo64, const __grid_constant__ CUtensorMap mo56,
                 const __nv_bfloat16* __restrict__ gamma, const __nv_bfloat16* __restrict__ beta,
                 const __nv_bfloat16* __restrict__ xg, const __nv_bfloat16* __restrict__ wgt, int mode) {
  extern __shared__ uint8_t smem_raw[];
  const uint32_t sb = (smem_u32(smem_raw) + 1023u) & ~1023u;
  const uint32_t bar = sb + OFF_BAR;
  const int tid = threadIdx.x, warp = tid >> 5, lane = tid & 31;
  const int rank = blockIdx.x & 1;
  const int cl = blockIdx.x >> 1;
  const int b = cl / TILES, tile = cl % TILES;
  const int l0 = tile * NT;
  STAMP(0);

  if (tid == 0) {
    asm volatile("prefetch.tensormap [%0];" ::"l"(&mx) : "memory");
    asm volatile("prefetch.tensormap [%0];" ::"l"(&mw) : "memory");
  }
  if (tid == 256) {
    for (int s = 0; s < 2; s++) {
      for (int k = 0; k < 3; k++) mbar_init(bar + 8 * (s * 3 + k), 1);
      mbar_init(bar + 48 + 8 * (s * 3 + 0), 2);
      mbar_init(bar + 48 + 8 * (s * 3 + 1), 4);
      mbar_init(bar + 48 + 8 * (s * 3 + 2), 4);
    }
    for (int k = 0; k < 8; k++) mbar_init(bar + 96 + 8 * k, 4);
    STAMP(14);
    asm volatile("fence.mbarrier_init.release.cluster;" ::: "memory");
    STAMP(15);
  }
  __syncwarp();
  asm volatile("barrier.cluster.arrive.relaxed.aligned;" ::: "memory");
  STAMP(16);
  if (tid == 256) {
    const int dcol = rank * 128;
    mbar_expect_tx(bar, X_BYTES + W_BYTES);
    tma_w(sb + OFF_W, &mw, bar, dcol, 0);
    tma_w(sb + OFF_W + 8192, &mw, bar, dcol + 64, 0);
    mbar_expect_tx(bar + 8, W_BYTES);
    tma_w(sb + OFF_W + W_BYTES, &mw, bar + 8, dcol, 512);
    tma_w(sb + OFF_W + W_BYTES + 8192, &mw, bar + 8, dcol + 64, 512);
  }
  STAMP(17);
  __syncwarp();
  asm volatile("barrier.cluster.wait.acquire.aligned;" ::: "memory");
  STAMP(18);
  if (tid == 256) {
    const int dcol = rank * 128;
    tma_x(sb + OFF_E + rank * (128 * 128), &mx, bar, 0, 0, l0 + rank * 128, b);
    mbar_expect_tx(bar + 16, X_BYTES + W_BYTES);
    tma_x(sb + OFF_O + rank * (128 * 128), &mx, bar + 16, 0, 1, l0 + rank * 128, b);
    tma_w(sb + OFF_W + 2 * W_BYTES, &mw, bar + 16, dcol, 256);
    tma_w(sb + OFF_W + 2 * W_BYTES + 8192, &mw, bar + 16, dcol + 64, 256);
  }
  STAMP(19);

  if (warp >= 8) {
    asm volatile("setmaxnreg.dec.sync.aligned.u32 40;");
    if (tid == 256) {
      const int dcol = rank * 128;
      const uint32_t xoff = rank * (128 * 128);
      const int lr = l0 + rank * 128;
#pragma unroll
      for (int j = 1; j < 4; j++) {
        const int s = j & 1;
        const uint32_t base = sb + s * SET_BYTES;
        const uint32_t fA = bar + 8 * (s * 3), fB = fA + 8, fC = fA + 16;
        const uint32_t eA = fA + 48, eB = fA + 56, eC = fA + 64;
        if (j >= 2) mbar_wait(eA, 0);
        STAMP(1 + 3 * j);
        if (j == 1 && DELAY1) mbar_wait(bar, 0);
        mbar_expect_tx(fA, X_BYTES + W_BYTES);
        tma_w(base + OFF_W, &mw, fA, dcol, j * 64);
        tma_w(base + OFF_W + 8192, &mw, fA, dcol + 64, j * 64);
        if (j >= 2) mbar_wait_cl(eB, 0);
        STAMP(2 + 3 * j);
        tma_x(base + OFF_E + xoff, &mx, fA, j * 64, 0, lr, b);
        mbar_expect_tx(fB, W_BYTES);
        tma_w(base + OFF_W + W_BYTES, &mw, fB, dcol, 512 + j * 64);
        tma_w(base + OFF_W + W_BYTES + 8192, &mw, fB, dcol + 64, 512 + j * 64);
        if (j >= 2) mbar_wait_cl(eC, 0);
        STAMP(3 + 3 * j);
        mbar_expect_tx(fC, X_BYTES + W_BYTES);
        tma_x(base + OFF_O + xoff, &mx, fC, j * 64, 1, lr, b);
        tma_w(base + OFF_W + 2 * W_BYTES, &mw, fC, dcol, 256 + j * 64);
        tma_w(base + OFF_W + 2 * W_BYTES + 8192, &mw, fC, dcol + 64, 256 + j * 64);
      }
      STAMP(13);
      STAMP_FLUSH(40);
    }
    if (lane == 0 && warp < 10 && mode != 1) {
      const int wg = warp - 8;
      if (wg == 1) asm volatile("prefetch.tensormap [%0];" ::"l"(&mo64) : "memory");
#pragma unroll
      for (int q = 0; q < 4; q++) {
        mbar_wait(bar + 96 + 8 * (wg * 4 + q), 0);
        if (l0 + q * 64 < L_) {
          const uint32_t stage = sb + (q / 3) * SET_BYTES + OFF_W + (q % 3) * W_BYTES + wg * 8192;
          tma_store(q == 3 ? &mo56 : &mo64, stage, rank * 128 + wg * 64, l0 + q * 64, b);
          asm volatile("cp.async.bulk.commit_group;" ::: "memory");
        }
      }
      asm volatile("cp.async.bulk.wait_group.read 0;" ::: "memory");
    }
    __syncwarp();
    asm volatile("barrier.cluster.arrive.relaxed.aligned;\nbarrier.cluster.wait.aligned;" ::: "memory");
  } else {
    asm volatile("setmaxnreg.inc.sync.aligned.u32 232;");
    const int wg = warp >> 2, wq = warp & 3;
    const int grp = b * 2 + rank;
    const int chw = wg * 64 + wq * 16;
    unsigned long long* part = g_part + (size_t)grp * TILES * 128;
    unsigned long long oldw;
    asm volatile("ld.relaxed.gpu.global.b64 %0, [%1];" : "=l"(oldw) : "l"(part + tile * 128 + chw));
    const int r0 = lane >> 2;
    uint16_t g0r, g1r, b0r, b1r;
    asm volatile("ld.global.nc.b16 %0, [%1];" : "=h"(g0r) : "l"(gamma + rank * 128 + chw + r0));
    asm volatile("ld.global.nc.b16 %0, [%1];" : "=h"(g1r) : "l"(gamma + rank * 128 + chw + r0 + 8));
    asm volatile("ld.global.nc.b16 %0, [%1];" : "=h"(b0r) : "l"(beta + rank * 128 + chw + r0));
    asm volatile("ld.global.nc.b16 %0, [%1];" : "=h"(b1r) : "l"(beta + rank * 128 + chw + r0 + 8));

    STAMP(1);
    float acc[NREG];
    const bool elected = (tid & 127) == 0;
#pragma unroll
    for (int j = 0; j < 4; j++) {
      const int s = j & 1;
      const uint32_t ph = j >> 1;
      const uint32_t base = sb + s * SET_BYTES;
      const uint32_t fA = bar + 8 * (s * 3), fB = fA + 8, fC = fA + 16;
      const uint64_t dE = make_desc(base + OFF_E), dO = make_desc(base + OFF_O);
      const uint64_t dW = make_desc(base + OFF_W + wg * 8192);
      if (3 * j == STAG && wg == 1) {
        if (j == 2) {
          wg_wait<0>();
          if (elected) { uint32_t eC = bar + 48 + 8 * ((s ^ 1) * 3 + 2); mbar_arrive_cluster(eC, 0); mbar_arrive_cluster(eC, 1); }
        }
        asm volatile("bar.sync 3, 256;" ::: "memory");
      }
      CWAIT(fA, ph);
      STAMP(8 + 3 * j);
      wg_fence();
#pragma unroll
      for (int k = 0; k < 4; k++) MMA(acc, dW + k * 128, dE + k * 2, (j | k) != 0);
      wg_commit();
      if (j == 1 || (j == 2 && !(STAG == 6 && wg == 1))) {
        wg_wait<1>();
        if (elected) { uint32_t eC = bar + 48 + 8 * ((s ^ 1) * 3 + 2); mbar_arrive_cluster(eC, 0); mbar_arrive_cluster(eC, 1); }
      }
      if (3 * j + 1 == STAG && wg == 1) asm volatile("bar.sync 3, 256;" ::: "memory");
      CWAIT(fB, ph);
      STAMP(9 + 3 * j);
      wg_fence();
#pragma unroll
      for (int k = 0; k < 4; k++) MMA(acc, dW + (W_BYTES >> 4) + k * 128, dE + 8 + k * 2, 1);
      wg_commit();
      if (j < 2) {
        wg_wait<1>();
        if (elected) mbar_arrive_local(fA + 48);
      }
      if (3 * j + 2 == STAG && wg == 1) asm volatile("bar.sync 3, 256;" ::: "memory");
      CWAIT(fC, ph);
      STAMP(10 + 3 * j);
      wg_fence();
#pragma unroll
      for (int k = 0; k < 4; k++) MMA(acc, dW + (2 * W_BYTES >> 4) + k * 128, dO + k * 2, 1);
      wg_commit();
      if (j < 2) {
        wg_wait<1>();
        if (elected) { mbar_arrive_cluster(fB + 48, 0); mbar_arrive_cluster(fB + 48, 1); }
      }
    }
    if (STAG < 12 && wg == 0) asm volatile("bar.arrive 3, 256;" ::: "memory");
    wg_wait<0>();
    STAMP(2);
    asm volatile("barrier.cluster.arrive.relaxed.aligned;" ::: "memory");

    const uint32_t tag = ((uint32_t)(oldw >> 32) & 1u) ^ 1u;
    if (mode != 2) {
      float s0 = 0.f, q0 = 0.f, s1 = 0.f, q1 = 0.f;
      static_assert(L_ == T_ / 2 - 1 && (L_ - (TILES - 1) * NT) == 63, "tail handling assumes this geometry");
      if (tile == TILES - 1 && (lane & 3) == 3) { acc[4 * 7 + 1] = 0.f; acc[4 * 7 + 3] = 0.f; }
      {
        float sa[4] = {0.f, 0.f, 0.f, 0.f}, qa[4] = {0.f, 0.f, 0.f, 0.f};
        float sb_[4] = {0.f, 0.f, 0.f, 0.f}, qb[4] = {0.f, 0.f, 0.f, 0.f};
#pragma unroll
        for (int i = 0; i < NT / 8; i++) {
          const int u = (i & 1) * 2;
          sa[u] += acc[4 * i]; sa[u + 1] += acc[4 * i + 1];
          qa[u] = fmaf(acc[4 * i], acc[4 * i], qa[u]); qa[u + 1] = fmaf(acc[4 * i + 1], acc[4 * i + 1], qa[u + 1]);
          sb_[u] += acc[4 * i + 2]; sb_[u + 1] += acc[4 * i + 3];
          qb[u] = fmaf(acc[4 * i + 2], acc[4 * i + 2], qb[u]); qb[u + 1] = fmaf(acc[4 * i + 3], acc[4 * i + 3], qb[u + 1]);
        }
        s0 = (sa[0] + sa[1]) + (sa[2] + sa[3]); q0 = (qa[0] + qa[1]) + (qa[2] + qa[3]);
        s1 = (sb_[0] + sb_[1]) + (sb_[2] + sb_[3]); q1 = (qb[0] + qb[1]) + (qb[2] + qb[3]);
      }
#pragma unroll
      for (int o = 1; o <= 2; o <<= 1) {
        s0 += __shfl_xor_sync(~0u, s0, o); q0 += __shfl_xor_sync(~0u, q0, o);
        s1 += __shfl_xor_sync(~0u, s1, o); q1 += __shfl_xor_sync(~0u, q1, o);
      }
      if ((lane & 3) < 2) {
        const float sv = (lane & 1) ? s1 : s0, qv = (lane & 1) ? q1 : q0;
        const unsigned long long v = (unsigned long long)__float_as_uint(sv) |
                                     ((unsigned long long)((__float_as_uint(qv) & ~1u) | tag) << 32);
        asm volatile("st.relaxed.gpu.global.b64 [%0], %1;" ::"l"(part + tile * 128 + chw + r0 + 8 * (lane & 1)), "l"(v) : "memory");
      }
    }
    STAMP(3);
    float sc0 = 0.f, sh0 = 0.f, sc1 = 0.f, sh1 = 0.f;
    if (mode != 1) {
      const unsigned long long* src = part + chw + 2 * (lane & 7);
      constexpr int NI = (TILES + 3) / 4;
      float sa = 0.f, qa = 0.f, sb2 = 0.f, qb = 0.f;
      unsigned long long va[NI], vb[NI];
#pragma unroll
      for (int i = 0; i < NI; i++) { va[i] = 0; vb[i] = 0; }
      const long long tw0 = clock64();
      if (mode == 0) {
        bool d0 = false, d1 = lane != 0;
        while (true) {
          unsigned long long u;
          if (!d0) { asm volatile("ld.relaxed.gpu.global.b64 %0, [%1];" : "=l"(u) : "l"(part + lane * 128 + chw + SENT_CH) : "memory"); d0 = ((uint32_t)(u >> 32) & 1u) == tag; }
          if (!d1) { asm volatile("ld.relaxed.gpu.global.b64 %0, [%1];" : "=l"(u) : "l"(part + 32 * 128 + chw + SENT_CH) : "memory"); d1 = ((uint32_t)(u >> 32) & 1u) == tag; }
          if (__all_sync(~0u, d0 && d1) || clock64() - tw0 > WAIT_LIMIT) break;
        }
      }
      STAMP(6);
      static_assert(TILES == 33, "partial read pattern assumes 33 tiles");
      uint64_t pa = (uint64_t)(src + (lane >> 3) * 128);
      asm volatile("mov.b64 %0, %0;" : "+l"(pa));
      while (true) {
#pragma unroll
        for (int i = 0; i < NI - 1; i++)
          asm volatile("ld.relaxed.gpu.global.v2.b64 {%0, %1}, [%2];" : "=l"(va[i]), "=l"(vb[i]) : "l"(pa + i * 4096) : "memory");
        if (lane < 8)
          asm volatile("ld.relaxed.gpu.global.v2.b64 {%0, %1}, [%2];" : "=l"(va[NI - 1]), "=l"(vb[NI - 1]) : "l"(pa + (NI - 1) * 4096) : "memory");
        uint32_t all1 = ~0u, any1 = 0u;
#pragma unroll
        for (int i = 0; i < NI; i++) {
          if (i < NI - 1 || lane < 8) {
            all1 &= (uint32_t)(va[i] >> 32) & (uint32_t)(vb[i] >> 32);
            any1 |= (uint32_t)(va[i] >> 32) | (uint32_t)(vb[i] >> 32);
          }
        }
        const bool ok = tag ? (all1 & 1u) : !(any1 & 1u);
        if (__all_sync(~0u, ok) || mode == 2 || clock64() - tw0 > WAIT_LIMIT) break;
      }
#pragma unroll
      for (int i = 0; i < NI; i++) {
        const int t = (lane >> 3) + 4 * i;
        if (t < TILES) {
          sa += __uint_as_float((uint32_t)va[i]); qa += __uint_as_float((uint32_t)(va[i] >> 32));
          sb2 += __uint_as_float((uint32_t)vb[i]); qb += __uint_as_float((uint32_t)(vb[i] >> 32));
        }
      }
#pragma unroll
      for (int o = 8; o <= 16; o <<= 1) {
        sa += __shfl_xor_sync(~0u, sa, o); qa += __shfl_xor_sync(~0u, qa, o);
        sb2 += __shfl_xor_sync(~0u, sb2, o); qb += __shfl_xor_sync(~0u, qb, o);
      }
      const int p0 = r0 >> 1, p1 = 4 + (r0 >> 1);
      const float sA0 = __shfl_sync(~0u, sa, p0), sB0 = __shfl_sync(~0u, sb2, p0);
      const float qA0 = __shfl_sync(~0u, qa, p0), qB0 = __shfl_sync(~0u, qb, p0);
      const float sA1 = __shfl_sync(~0u, sa, p1), sB1 = __shfl_sync(~0u, sb2, p1);
      const float qA1 = __shfl_sync(~0u, qa, p1), qB1 = __shfl_sync(~0u, qb, p1);
      const float invL = 1.0f / (float)L_;
      const float m0 = ((r0 & 1) ? sB0 : sA0) * invL, m1 = ((r0 & 1) ? sB1 : sA1) * invL;
      const float v0 = fmaxf(((r0 & 1) ? qB0 : qA0) * invL - m0 * m0, 0.f);
      const float v1 = fmaxf(((r0 & 1) ? qB1 : qA1) * invL - m1 * m1, 0.f);
      const float rs0 = rsqrtf(v0 + 1e-5f), rs1 = rsqrtf(v1 + 1e-5f);
      const float g0 = __uint_as_float((uint32_t)g0r << 16), g1 = __uint_as_float((uint32_t)g1r << 16);
      const float be0 = __uint_as_float((uint32_t)b0r << 16), be1 = __uint_as_float((uint32_t)b1r << 16);
      sc0 = 0.5f * rs0 * g0; sh0 = 0.5f * be0 - m0 * sc0;
      sc1 = 0.5f * rs1 * g1; sh1 = 0.5f * be1 - m1 * sc1;
      STAMP(4);

      asm volatile("bar.sync %0, 128;" ::"r"(1 + wg) : "memory");
      const int mrow = lane & 7, mi = lane >> 3;
      const uint32_t chunk = (uint32_t)(2 * wq + (mi & 1));
      const uint32_t lane_off = (uint32_t)(((mi >> 1) * 8 + mrow) * 128) + ((chunk ^ (uint32_t)mrow) << 4);
#pragma unroll
      for (int q = 0; q < 4; q++) {
        const uint32_t stage = sb + (q / 3) * SET_BYTES + OFF_W + (q % 3) * W_BYTES + wg * 8192;
        constexpr int NG_FULL = 8;
        const int ng = (q == 3) ? (NT / 8 - 24) : NG_FULL;
#pragma unroll
        for (int ii = 0; ii < NG_FULL; ii += 2) {
          if (ii < ng) {
            const int i = q * 8 + ii;
            const uint32_t a0 = pack_bf16(gelu_half(fmaf(acc[4 * i], sc0, sh0)), gelu_half(fmaf(acc[4 * i + 1], sc0, sh0)));
            const uint32_t a1 = pack_bf16(gelu_half(fmaf(acc[4 * i + 2], sc1, sh1)), gelu_half(fmaf(acc[4 * i + 3], sc1, sh1)));
            if (ii + 1 < ng) {
              const int i2 = (i + 1 < NT / 8) ? i + 1 : i;
              const uint32_t a2 = pack_bf16(gelu_half(fmaf(acc[4 * i2], sc0, sh0)), gelu_half(fmaf(acc[4 * i2 + 1], sc0, sh0)));
              const uint32_t a3 = pack_bf16(gelu_half(fmaf(acc[4 * i2 + 2], sc1, sh1)), gelu_half(fmaf(acc[4 * i2 + 3], sc1, sh1)));
              asm volatile("stmatrix.sync.aligned.m8n8.x4.trans.shared.b16 [%0], {%1, %2, %3, %4};"
                           ::"r"(stage + ii * 1024 + lane_off), "r"(a0), "r"(a1), "r"(a2), "r"(a3) : "memory");
            } else {
              asm volatile("stmatrix.sync.aligned.m8n8.x2.trans.shared.b16 [%0], {%1, %2};"
                           ::"r"(stage + ii * 1024 + lane_off), "r"(a0), "r"(a1) : "memory");
            }
          }
        }
        asm volatile("fence.proxy.async.shared::cta;" ::: "memory");
        __syncwarp();
        if (lane == 0) mbar_arrive_local(bar + 96 + 8 * (wg * 4 + q));
      }
      STAMP(5);
    }
    asm volatile("barrier.cluster.wait.aligned;" ::: "memory");
    STAMP(7);
    if (elected) STAMP_FLUSH(20 * wg);
  }
}

typedef CUresult (*EncodeFn)(CUtensorMap*, CUtensorMapDataType, cuuint32_t, void*, const cuuint64_t*, const cuuint64_t*,
                             const cuuint32_t*, const cuuint32_t*, CUtensorMapInterleave, CUtensorMapSwizzle,
                             CUtensorMapL2promotion, CUtensorMapFloatOOBfill);

}

extern "C" void kernel_launch(void* const* d_in, const int* in_sizes, int n_in, void* d_out, int out_size) {
  (void)in_sizes; (void)n_in; (void)out_size;
  static EncodeFn encode = nullptr;
  static int fused = 0;
  static CUtensorMap mx, mw, mo64, mo56;
  static void* cached[3] = {nullptr, nullptr, nullptr};
  cudaLaunchConfig_t cfg = {};
  cudaLaunchAttribute attr[1];
  cfg.gridDim = dim3(NCTA); cfg.blockDim = dim3(NTHREADS); cfg.dynamicSmemBytes = SMEM_BYTES;
  cfg.stream = cudaStreamPerThread;
  attr[0].id = cudaLaunchAttributeClusterDimension;
  attr[0].val.clusterDim.x = 2; attr[0].val.clusterDim.y = 1; attr[0].val.clusterDim.z = 1;
  cfg.attrs = attr; cfg.numAttrs = 1;
  if (!encode) {
    void* fn = nullptr;
    cudaDriverEntryPointQueryResult qr;
    cudaGetDriverEntryPoint("cuTensorMapEncodeTiled", &fn, cudaEnableDefault, &qr);
    encode = (EncodeFn)fn;
    cudaFuncSetAttribute(conv_stem_kernel, cudaFuncAttributeMaxDynamicSharedMemorySize, SMEM_BYTES);
    int ncl = 0;
    cudaError_t e = cudaOccupancyMaxActiveClusters(&ncl, conv_stem_kernel, &cfg);
    fused = (e == cudaSuccess && ncl >= NCTA / 2) ? 1 : 0;
    (void)cudaGetLastError();
  }
  if (cached[0] != d_in[0] || cached[1] != d_in[1] || cached[2] != d_out) {
    cached[0] = d_in[0]; cached[1] = d_in[1]; cached[2] = d_out;
    {
      cuuint64_t dims[4] = {D_, 2, T_ / 2, B_};
      cuuint64_t str[3] = {D_ * 2, D_ * 4, (cuuint64_t)T_ * D_ * 2};
      cuuint32_t box[4] = {64, 1, 128, 1}, es[4] = {1, 1, 1, 1};
      encode(&mx, CU_TENSOR_MAP_DATA_TYPE_BFLOAT16, 4, d_in[0], dims, str, box, es, CU_TENSOR_MAP_INTERLEAVE_NONE,
             CU_TENSOR_MAP_SWIZZLE_128B, XPROMO, CU_TENSOR_MAP_FLOAT_OOB_FILL_NONE);
    }
    {
      cuuint64_t dims[2] = {D_, 3 * D_};
      cuuint64_t str[1] = {D_ * 2};
      cuuint32_t box[2] = {64, 64}, es[2] = {1, 1};
      encode(&mw, CU_TENSOR_MAP_DATA_TYPE_BFLOAT16, 2, d_in[1], dims, str, box, es, CU_TENSOR_MAP_INTERLEAVE_NONE,
             CU_TENSOR_MAP_SWIZZLE_128B, CU_TENSOR_MAP_L2_PROMOTION_L2_256B, CU_TENSOR_MAP_FLOAT_OOB_FILL_NONE);
    }
    for (int v = 0; v < 2; v++) {
      cuuint64_t dims[3] = {D_, L_, B_};
      cuuint64_t str[2] = {D_ * 2, (cuuint64_t)L_ * D_ * 2};
      cuuint32_t box[3] = {64, (cuuint32_t)(v ? NT - 192 : 64), 1}, es[3] = {1, 1, 1};
      encode(v ? &mo56 : &mo64, CU_TENSOR_MAP_DATA_TYPE_BFLOAT16, 3, d_out, dims, str, box, es,
             CU_TENSOR_MAP_INTERLEAVE_NONE, CU_TENSOR_MAP_SWIZZLE_128B, CU_TENSOR_MAP_L2_PROMOTION_NONE,
             CU_TENSOR_MAP_FLOAT_OOB_FILL_NONE);
    }
  }
  const __nv_bfloat16* gamma = (const __nv_bfloat16*)d_in[2];
  const __nv_bfloat16* beta = (const __nv_bfloat16*)d_in[3];
  const __nv_bfloat16* xg = (const __nv_bfloat16*)d_in[0];
  const __nv_bfloat16* wgt = (const __nv_bfloat16*)d_in[1];
  if (fused) {
    cudaLaunchKernelEx(&cfg, conv_stem_kernel, mx, mw, mo64, mo56, gamma, beta, xg, wgt, 0);
  } else {
    cudaLaunchKernelEx(&cfg, conv_stem_kernel, mx, mw, mo64, mo56, gamma, beta, xg, wgt, 1);
    cudaLaunchKernelEx(&cfg, conv_stem_kernel, mx, mw, mo64, mo56, gamma, beta, xg, wgt, 2);
  }
}
```

```cpp
#include <cuda_runtime.h>
#include <cuda_bf16.h>
#include <cuda.h>
#include <stdint.h>

namespace {

constexpr int B_ = 2, T_ = 16000, D_ = 256, L_ = 7999;
constexpr int NT = 248;
constexpr int TILES = 33;
constexpr int NREG = NT / 2;
constexpr int NCTA = B_ * TILES * 2;
constexpr int NTHREADS = 384;

constexpr int X_BYTES = 256 * 128;
constexpr int W_BYTES = 2 * 64 * 128;
constexpr int SET_BYTES = 2 * X_BYTES + 3 * W_BYTES;
constexpr int OFF_E = 0, OFF_O = X_BYTES, OFF_W = 2 * X_BYTES;
constexpr int OFF_BAR = 2 * SET_BYTES;
constexpr int SMEM_BYTES = OFF_BAR + 256 + 1024;

__device__ unsigned long long g_part[4 * TILES * 128];
#define STAMP(i)
#define STAMP_FLUSH(base)

__device__ __forceinline__ uint32_t smem_u32(const void* p) { return (uint32_t)__cvta_generic_to_shared(p); }
__device__ __forceinline__ void mbar_init(uint32_t bar, uint32_t cnt) {
  asm volatile("mbarrier.init.shared::cta.b64 [%0], %1;" ::"r"(bar), "r"(cnt) : "memory");
}
__device__ __forceinline__ void mbar_expect_tx(uint32_t bar, uint32_t bytes) {
  asm volatile("mbarrier.arrive.expect_tx.shared::cta.b64 _, [%0], %1;" ::"r"(bar), "r"(bytes) : "memory");
}
__device__ __forceinline__ bool mbar_try(uint32_t bar, uint32_t parity) {
  uint32_t ok;
  asm volatile("{\n.reg .pred p;\nmbarrier.try_wait.parity.shared::cta.b64 p, [%1], %2;\nselp.u32 %0, 1, 0, p;\n}"
               : "=r"(ok) : "r"(bar), "r"(parity) : "memory");
  return ok;
}
__device__ __forceinline__ bool mbar_try_cl(uint32_t bar, uint32_t parity) {
  uint32_t ok;
  asm volatile("{\n.reg .pred p;\nmbarrier.try_wait.parity.acquire.cluster.shared::cta.b64 p, [%1], %2;\nselp.u32 %0, 1, 0, p;\n}"
               : "=r"(ok) : "r"(bar), "r"(parity) : "memory");
  return ok;
}
constexpr long long WAIT_LIMIT = 100000000ll;
__device__ __forceinline__ void mbar_wait(uint32_t bar, uint32_t parity) {
  if (mbar_try(bar, parity)) return;
  const long long t0 = clock64();
  while (!mbar_try(bar, parity)) if (clock64() - t0 > WAIT_LIMIT) return;
}
__device__ __forceinline__ void mbar_wait_cl(uint32_t bar, uint32_t parity) {
  if (mbar_try_cl(bar, parity)) return;
  const long long t0 = clock64();
  while (!mbar_try_cl(bar, parity)) if (clock64() - t0 > WAIT_LIMIT) return;
}
__device__ __forceinline__ void mbar_arrive_local(uint32_t bar) {
  asm volatile("mbarrier.arrive.shared::cta.b64 _, [%0];" ::"r"(bar) : "memory");
}
__device__ __forceinline__ void mbar_arrive_cluster(uint32_t bar, uint32_t cta) {
  asm volatile("{\n.reg .b32 r;\nmapa.shared::cluster.u32 r, %0, %1;\n"
               "mbarrier.arrive.shared::cluster.b64 _, [r];\n}" ::"r"(bar), "r"(cta) : "memory");
}
__device__ __forceinline__ void tma_x(uint32_t dst, const CUtensorMap* m, uint32_t bar, int c, int par, int l, int b) {
  asm volatile("cp.async.bulk.tensor.4d.shared::cluster.global.mbarrier::complete_tx::bytes.multicast::cluster "
               "[%0], [%1, {%3, %4, %5, %6}], [%2], %7;"
               ::"r"(dst), "l"(m), "r"(bar), "r"(c), "r"(par), "r"(l), "r"(b), "h"((uint16_t)3) : "memory");
}
__device__ __forceinline__ void tma_w(uint32_t dst, const CUtensorMap* m, uint32_t bar, int d, int row) {
  asm volatile("cp.async.bulk.tensor.2d.shared::cluster.global.mbarrier::complete_tx::bytes "
               "[%0], [%1, {%3, %4}], [%2];"
               ::"r"(dst), "l"(m), "r"(bar), "r"(d), "r"(row) : "memory");
}
__device__ __forceinline__ void tma_store(const CUtensorMap* m, uint32_t src, int d, int l, int b) {
  asm volatile("cp.async.bulk.tensor.3d.global.shared::cta.bulk_group [%0, {%2, %3, %4}], [%1];"
               ::"l"(m), "r"(src), "r"(d), "r"(l), "r"(b) : "memory");
}
__device__ __forceinline__ uint64_t make_desc(uint32_t addr) {
  return (uint64_t)((addr & 0x3FFFF) >> 4) | ((uint64_t)1 << 16) | ((uint64_t)64 << 32) | ((uint64_t)1 << 62);
}
__device__ __forceinline__ void wg_fence() { asm volatile("wgmma.fence.sync.aligned;" ::: "memory"); }
__device__ __forceinline__ void wg_commit() { asm volatile("wgmma.commit_group.sync.aligned;" ::: "memory"); }
template <int N> __device__ __forceinline__ void wg_wait() { asm volatile("wgmma.wait_group.sync.aligned %0;" ::"n"(N) : "memory"); }
__device__ __forceinline__ float tanh_fast(float x) { float y; asm("tanh.approx.f32 %0, %1;" : "=f"(y) : "f"(x)); return y; }
__device__ __forceinline__ uint32_t pack_bf16(float lo, float hi) {
  uint32_t r; asm("cvt.rn.bf16x2.f32 %0, %1, %2;" : "=r"(r) : "f"(hi), "f"(lo)); return r;
}
__device__ __forceinline__ float gelu_half(float hh) {
  const float c1 = 2.0f * 0.7978845608028654f, c3 = 8.0f * 0.7978845608028654f * 0.044715f;
  float u = hh * fmaf(hh * hh, c3, c1);
  return fmaf(hh, tanh_fast(u), hh);
}

#define STAG 6
#define FORCE_SPLIT 0

__device__ __forceinline__ void wgmma_n248(float (&d)[124], uint64_t da, uint64_t db, int scale_d) {
  asm volatile("{\n.reg .pred p;\nsetp.ne.b32 p, %126, 0;\n"
    "wgmma.mma_async.sync.aligned.m64n248k16.f32.bf16.bf16 "
    "{%0, %1, %2, %3, %4, %5, %6, %7, %8, %9, %10, %11, %12, %13, %14, %15, "
    "%16, %17, %18, %19, %20, %21, %22, %23, %24, %25, %26, %27, %28, %29, %30, %31, "
    "%32, %33, %34, %35, %36, %37, %38, %39, %40, %41, %42, %43, %44, %45, %46, %47, "
    "%48, %49, %50, %51, %52, %53, %54, %55, %56, %57, %58, %59, %60, %61, %62, %63, "
    "%64, %65, %66, %67, %68, %69, %70, %71, %72, %73, %74, %75, %76, %77, %78, %79, "
    "%80, %81, %82, %83, %84, %85, %86, %87, %88, %89, %90, %91, %92, %93, %94, %95, "
    "%96, %97, %98, %99, %100, %101, %102, %103, %104, %105, %106, %107, %108, %109, %110, %111, "
    "%112, %113, %114, %115, %116, %117, %118, %119, %120, %121, %122, %123}, "
    "%124, %125, p, 1, 1, 1, 0;\n}\n"
    : "+f"(d[0]), "+f"(d[1]), "+f"(d[2]), "+f"(d[3]), "+f"(d[4]), "+f"(d[5]), "+f"(d[6]), "+f"(d[7]),
      "+f"(d[8]), "+f"(d[9]), "+f"(d[10]), "+f"(d[11]), "+f"(d[12]), "+f"(d[13]), "+f"(d[14]), "+f"(d[15]),
      "+f"(d[16]), "+f"(d[17]), "+f"(d[18]), "+f"(d[19]), "+f"(d[20]), "+f"(d[21]), "+f"(d[22]), "+f"(d[23]),
      "+f"(d[24]), "+f"(d[25]), "+f"(d[26]), "+f"(d[27]), "+f"(d[28]), "+f"(d[29]), "+f"(d[30]), "+f"(d[31]),
      "+f"(d[32]), "+f"(d[33]), "+f"(d[34]), "+f"(d[35]), "+f"(d[36]), "+f"(d[37]), "+f"(d[38]), "+f"(d[39]),
      "+f"(d[40]), "+f"(d[41]), "+f"(d[42]), "+f"(d[43]), "+f"(d[44]), "+f"(d[45]), "+f"(d[46]), "+f"(d[47]),
      "+f"(d[48]), "+f"(d[49]), "+f"(d[50]), "+f"(d[51]), "+f"(d[52]), "+f"(d[53]), "+f"(d[54]), "+f"(d[55]),
      "+f"(d[56]), "+f"(d[57]), "+f"(d[58]), "+f"(d[59]), "+f"(d[60]), "+f"(d[61]), "+f"(d[62]), "+f"(d[63]),
      "+f"(d[64]), "+f"(d[65]), "+f"(d[66]), "+f"(d[67]), "+f"(d[68]), "+f"(d[69]), "+f"(d[70]), "+f"(d[71]),
      "+f"(d[72]), "+f"(d[73]), "+f"(d[74]), "+f"(d[75]), "+f"(d[76]), "+f"(d[77]), "+f"(d[78]), "+f"(d[79]),
      "+f"(d[80]), "+f"(d[81]), "+f"(d[82]), "+f"(d[83]), "+f"(d[84]), "+f"(d[85]), "+f"(d[86]), "+f"(d[87]),
      "+f"(d[88]), "+f"(d[89]), "+f"(d[90]), "+f"(d[91]), "+f"(d[92]), "+f"(d[93]), "+f"(d[94]), "+f"(d[95]),
      "+f"(d[96]), "+f"(d[97]), "+f"(d[98]), "+f"(d[99]), "+f"(d[100]), "+f"(d[101]), "+f"(d[102]), "+f"(d[103]),
      "+f"(d[104]), "+f"(d[105]), "+f"(d[106]), "+f"(d[107]), "+f"(d[108]), "+f"(d[109]), "+f"(d[110]), "+f"(d[111]),
      "+f"(d[112]), "+f"(d[113]), "+f"(d[114]), "+f"(d[115]), "+f"(d[116]), "+f"(d[117]), "+f"(d[118]), "+f"(d[119]),
      "+f"(d[120]), "+f"(d[121]), "+f"(d[122]), "+f"(d[123])
    : "l"(da), "l"(db), "r"(scale_d));
}

__global__ void __launch_bounds__(NTHREADS, 1)
conv_stem_kernel(const __grid_constant__ CUtensorMap mx, const __grid_constant__ CUtensorMap mw,
                 const __grid_constant__ CUtensorMap mo64, const __grid_constant__ CUtensorMap mo56,
                 const __nv_bfloat16* __restrict__ gamma, const __nv_bfloat16* __restrict__ beta, int mode) {
  extern __shared__ uint8_t smem_raw[];
  const uint32_t sb = (smem_u32(smem_raw) + 1023u) & ~1023u;
  const uint32_t bar = sb + OFF_BAR;
  const int tid = threadIdx.x, warp = tid >> 5, lane = tid & 31;
  const int rank = blockIdx.x & 1;
  const int cl = blockIdx.x >> 1;
  const int b = cl / TILES, tile = cl % TILES;
  const int l0 = tile * NT;
  STAMP(0);

  if (tid == 0) {
    asm volatile("prefetch.tensormap [%0];" ::"l"(&mx) : "memory");
    asm volatile("prefetch.tensormap [%0];" ::"l"(&mw) : "memory");
  }
  if (tid == 256) {
    for (int s = 0; s < 2; s++) {
      for (int k = 0; k < 3; k++) mbar_init(bar + 8 * (s * 3 + k), 1);
      mbar_init(bar + 48 + 8 * (s * 3 + 0), 2);
      mbar_init(bar + 48 + 8 * (s * 3 + 1), 4);
      mbar_init(bar + 48 + 8 * (s * 3 + 2), 4);
    }
    for (int k = 0; k < 8; k++) mbar_init(bar + 96 + 8 * k, 4);
    STAMP(14);
    asm volatile("fence.mbarrier_init.release.cluster;" ::: "memory");
    STAMP(15);
  }
  __syncwarp();
  asm volatile("barrier.cluster.arrive.relaxed.aligned;" ::: "memory");
  STAMP(16);
  if (tid == 256) {
    const int dcol = rank * 128;
    mbar_expect_tx(bar, X_BYTES + W_BYTES);
    tma_w(sb + OFF_W, &mw, bar, dcol, 0);
    tma_w(sb + OFF_W + 8192, &mw, bar, dcol + 64, 0);
    mbar_expect_tx(bar + 8, W_BYTES);
    tma_w(sb + OFF_W + W_BYTES, &mw, bar + 8, dcol, 512);
    tma_w(sb + OFF_W + W_BYTES + 8192, &mw, bar + 8, dcol + 64, 512);
  }
  STAMP(17);
  __syncwarp();
  asm volatile("barrier.cluster.wait.acquire.aligned;" ::: "memory");
  STAMP(18);
  if (tid == 256) {
    const int dcol = rank * 128;
    tma_x(sb + OFF_E + rank * (128 * 128), &mx, bar, 0, 0, l0 + rank * 128, b);
    mbar_expect_tx(bar + 16, X_BYTES + W_BYTES);
    tma_x(sb + OFF_O + rank * (128 * 128), &mx, bar + 16, 0, 1, l0 + rank * 128, b);
    tma_w(sb + OFF_W + 2 * W_BYTES, &mw, bar + 16, dcol, 256);
    tma_w(sb + OFF_W + 2 * W_BYTES + 8192, &mw, bar + 16, dcol + 64, 256);
  }
  STAMP(19);

  if (warp >= 8) {
    asm volatile("setmaxnreg.dec.sync.aligned.u32 40;");
    if (tid == 256) {
      const int dcol = rank * 128;
      const uint32_t xoff = rank * (128 * 128);
      const int lr = l0 + rank * 128;
#pragma unroll
      for (int j = 1; j < 4; j++) {
        const int s = j & 1;
        const uint32_t base = sb + s * SET_BYTES;
        const uint32_t fA = bar + 8 * (s * 3), fB = fA + 8, fC = fA + 16;
        const uint32_t eA = fA + 48, eB = fA + 56, eC = fA + 64;
        if (j >= 2) mbar_wait(eA, 0);
        STAMP(1 + 3 * j);
        if (j == 1) mbar_wait(bar, 0);
        mbar_expect_tx(fA, X_BYTES + W_BYTES);
        tma_w(base + OFF_W, &mw, fA, dcol, j * 64);
        tma_w(base + OFF_W + 8192, &mw, fA, dcol + 64, j * 64);
        if (j >= 2) mbar_wait_cl(eB, 0);
        STAMP(2 + 3 * j);
        tma_x(base + OFF_E + xoff, &mx, fA, j * 64, 0, lr, b);
        mbar_expect_tx(fB, W_BYTES);
        tma_w(base + OFF_W + W_BYTES, &mw, fB, dcol, 512 + j * 64);
        tma_w(base + OFF_W + W_BYTES + 8192, &mw, fB, dcol + 64, 512 + j * 64);
        if (j >= 2) mbar_wait_cl(eC, 0);
        STAMP(3 + 3 * j);
        mbar_expect_tx(fC, X_BYTES + W_BYTES);
        tma_x(base + OFF_O + xoff, &mx, fC, j * 64, 1, lr, b);
        tma_w(base + OFF_W + 2 * W_BYTES, &mw, fC, dcol, 256 + j * 64);
        tma_w(base + OFF_W + 2 * W_BYTES + 8192, &mw, fC, dcol + 64, 256 + j * 64);
      }
      STAMP(13);
      STAMP_FLUSH(40);
    }
    if (lane == 0 && warp < 10 && mode != 1) {
      const int wg = warp - 8;
      if (wg == 1) asm volatile("prefetch.tensormap [%0];" ::"l"(&mo64) : "memory");
#pragma unroll
      for (int q = 0; q < 4; q++) {
        mbar_wait(bar + 96 + 8 * (wg * 4 + q), 0);
        if (l0 + q * 64 < L_) {
          const uint32_t stage = sb + (q / 3) * SET_BYTES + OFF_W + (q % 3) * W_BYTES + wg * 8192;
          tma_store(q == 3 ? &mo56 : &mo64, stage, rank * 128 + wg * 64, l0 + q * 64, b);
          asm volatile("cp.async.bulk.commit_group;" ::: "memory");
        }
      }
      asm volatile("cp.async.bulk.wait_group.read 0;" ::: "memory");
    }
    __syncwarp();
    asm volatile("barrier.cluster.arrive.relaxed.aligned;\nbarrier.cluster.wait.aligned;" ::: "memory");
  } else {
    asm volatile("setmaxnreg.inc.sync.aligned.u32 232;");
    const int wg = warp >> 2, wq = warp & 3;
    const int grp = b * 2 + rank;
    const int chw = wg * 64 + wq * 16;
    unsigned long long* part = g_part + (size_t)grp * TILES * 128;
    unsigned long long oldw;
    asm volatile("ld.relaxed.gpu.global.b64 %0, [%1];" : "=l"(oldw) : "l"(part + tile * 128 + chw));
    const int r0 = lane >> 2;
    uint16_t g0r, g1r, b0r, b1r;
    asm volatile("ld.global.nc.b16 %0, [%1];" : "=h"(g0r) : "l"(gamma + rank * 128 + chw + r0));
    asm volatile("ld.global.nc.b16 %0, [%1];" : "=h"(g1r) : "l"(gamma + rank * 128 + chw + r0 + 8));
    asm volatile("ld.global.nc.b16 %0, [%1];" : "=h"(b0r) : "l"(beta + rank * 128 + chw + r0));
    asm volatile("ld.global.nc.b16 %0, [%1];" : "=h"(b1r) : "l"(beta + rank * 128 + chw + r0 + 8));

    STAMP(1);
    float acc[NREG];
    const bool elected = (tid & 127) == 0;
#pragma unroll
    for (int j = 0; j < 4; j++) {
      const int s = j & 1;
      const uint32_t ph = j >> 1;
      const uint32_t base = sb + s * SET_BYTES;
      const uint32_t fA = bar + 8 * (s * 3), fB = fA + 8, fC = fA + 16;
      const uint64_t dE = make_desc(base + OFF_E), dO = make_desc(base + OFF_O);
      const uint64_t dW = make_desc(base + OFF_W + wg * 8192);
      if (3 * j == STAG && wg == 1) {
        if (j == 2) {
          wg_wait<0>();
          if (elected) { uint32_t eC = bar + 48 + 8 * ((s ^ 1) * 3 + 2); mbar_arrive_cluster(eC, 0); mbar_arrive_cluster(eC, 1); }
        }
        asm volatile("bar.sync 3, 256;" ::: "memory");
      }
      mbar_wait(fA, ph);
      STAMP(8 + 3 * j);
      wg_fence();
#pragma unroll
      for (int k = 0; k < 4; k++) wgmma_n248(acc, dW + k * 128, dE + k * 2, (j | k) != 0);
      wg_commit();
      if (j == 1 || (j == 2 && !(STAG == 6 && wg == 1))) {
        wg_wait<1>();
        if (elected) { uint32_t eC = bar + 48 + 8 * ((s ^ 1) * 3 + 2); mbar_arrive_cluster(eC, 0); mbar_arrive_cluster(eC, 1); }
      }
      if (j == 1 && mode != 2 && (lane & 3) < 2) {
        const unsigned long long inv = (unsigned long long)((uint32_t)(oldw >> 32) & 1u) << 32;
        asm volatile("st.relaxed.gpu.global.b64 [%0], %1;" ::"l"(part + tile * 128 + chw + r0 + 8 * (lane & 1)), "l"(inv) : "memory");
      }
      if (3 * j + 1 == STAG && wg == 1) asm volatile("bar.sync 3, 256;" ::: "memory");
      mbar_wait(fB, ph);
      STAMP(9 + 3 * j);
      wg_fence();
#pragma unroll
      for (int k = 0; k < 4; k++) wgmma_n248(acc, dW + (W_BYTES >> 4) + k * 128, dE + 8 + k * 2, 1);
      wg_commit();
      if (j < 2) {
        wg_wait<1>();
        if (elected) mbar_arrive_local(fA + 48);
      }
      if (3 * j + 2 == STAG && wg == 1) asm volatile("bar.sync 3, 256;" ::: "memory");
      mbar_wait(fC, ph);
      STAMP(10 + 3 * j);
      wg_fence();
#pragma unroll
      for (int k = 0; k < 4; k++) wgmma_n248(acc, dW + (2 * W_BYTES >> 4) + k * 128, dO + k * 2, 1);
      wg_commit();
      if (j < 2) {
        wg_wait<1>();
        if (elected) { mbar_arrive_cluster(fB + 48, 0); mbar_arrive_cluster(fB + 48, 1); }
      }
    }
    if (STAG < 12 && wg == 0) asm volatile("bar.arrive 3, 256;" ::: "memory");
    wg_wait<0>();
    STAMP(2);
    asm volatile("barrier.cluster.arrive.relaxed.aligned;" ::: "memory");

    const uint32_t tag = ((uint32_t)(oldw >> 32) & 1u) ^ 1u;
    static_assert(TILES == 33, "partial read pattern assumes 33 tiles");
    constexpr int NI = (TILES + 3) / 4;
    unsigned long long va[NI], vb[NI];
    const uint32_t tagx = tag ^ 1u;
    uint64_t pa = (uint64_t)(part + chw + 2 * (lane & 7) + (lane >> 3) * 128);
    asm volatile("mov.b64 %0, %0;" : "+l"(pa));
    uint32_t pend = (lane < 8) ? ((1u << NI) - 1u) : ((1u << (NI - 1)) - 1u);
#pragma unroll
    for (int i = 0; i < NI; i++) { va[i] = 0; vb[i] = 0; }
    if (mode != 2) {
      float s0 = 0.f, q0 = 0.f, s1 = 0.f, q1 = 0.f;
      static_assert(L_ == T_ / 2 - 1 && (L_ - (TILES - 1) * NT) == 63, "tail handling assumes this geometry");
      if (tile == TILES - 1 && (lane & 3) == 3) { acc[4 * 7 + 1] = 0.f; acc[4 * 7 + 3] = 0.f; }
      {
        float sa[4] = {0.f, 0.f, 0.f, 0.f}, qa[4] = {0.f, 0.f, 0.f, 0.f};
        float sb_[4] = {0.f, 0.f, 0.f, 0.f}, qb[4] = {0.f, 0.f, 0.f, 0.f};
#pragma unroll
        for (int i = 0; i < NT / 8; i++) {
          const int u = (i & 1) * 2;
          sa[u] += acc[4 * i]; sa[u + 1] += acc[4 * i + 1];
          qa[u] = fmaf(acc[4 * i], acc[4 * i], qa[u]); qa[u + 1] = fmaf(acc[4 * i + 1], acc[4 * i + 1], qa[u + 1]);
          sb_[u] += acc[4 * i + 2]; sb_[u + 1] += acc[4 * i + 3];
          qb[u] = fmaf(acc[4 * i + 2], acc[4 * i + 2], qb[u]); qb[u + 1] = fmaf(acc[4 * i + 3], acc[4 * i + 3], qb[u + 1]);
        }
        s0 = (sa[0] + sa[1]) + (sa[2] + sa[3]); q0 = (qa[0] + qa[1]) + (qa[2] + qa[3]);
        s1 = (sb_[0] + sb_[1]) + (sb_[2] + sb_[3]); q1 = (qb[0] + qb[1]) + (qb[2] + qb[3]);
      }
#pragma unroll
      for (int o = 1; o <= 2; o <<= 1) {
        s0 += __shfl_xor_sync(~0u, s0, o); q0 += __shfl_xor_sync(~0u, q0, o);
        s1 += __shfl_xor_sync(~0u, s1, o); q1 += __shfl_xor_sync(~0u, q1, o);
      }
      if ((lane & 3) < 2) {
        const float sv = (lane & 1) ? s1 : s0, qv = (lane & 1) ? q1 : q0;
        const unsigned long long v = (unsigned long long)__float_as_uint(sv) |
                                     ((unsigned long long)((__float_as_uint(qv) & ~1u) | tag) << 32);
        asm volatile("st.relaxed.gpu.global.b64 [%0], %1;" ::"l"(part + tile * 128 + chw + r0 + 8 * (lane & 1)), "l"(v) : "memory");
      }
    }
    STAMP(3);
    float sc0 = 0.f, sh0 = 0.f, sc1 = 0.f, sh1 = 0.f;
    if (mode != 1) {
      const long long tw0 = clock64();
      float sa = 0.f, qa = 0.f, sb2 = 0.f, qb = 0.f;
      while (true) {
#pragma unroll
        for (int i = 0; i < NI; i++)
          if (pend & (1u << i))
            asm volatile("ld.relaxed.gpu.global.v2.b64 {%0, %1}, [%2];" : "=l"(va[i]), "=l"(vb[i]) : "l"(pa + i * 4096) : "memory");
#pragma unroll
        for (int i = 0; i < NI; i++) {
          const uint32_t ta = (uint32_t)(va[i] >> 32) ^ tagx, tb = (uint32_t)(vb[i] >> 32) ^ tagx;
          if ((ta & tb) & 1u) pend &= ~(1u << i);
        }
        if (__all_sync(~0u, pend == 0) || mode == 2 || clock64() - tw0 > WAIT_LIMIT) break;
      }
      STAMP(6);
#pragma unroll
      for (int i = 0; i < NI; i++) {
        const int t = (lane >> 3) + 4 * i;
        if (t < TILES) {
          sa += __uint_as_float((uint32_t)va[i]); qa += __uint_as_float((uint32_t)(va[i] >> 32));
          sb2 += __uint_as_float((uint32_t)vb[i]); qb += __uint_as_float((uint32_t)(vb[i] >> 32));
        }
      }
#pragma unroll
      for (int o = 8; o <= 16; o <<= 1) {
        sa += __shfl_xor_sync(~0u, sa, o); qa += __shfl_xor_sync(~0u, qa, o);
        sb2 += __shfl_xor_sync(~0u, sb2, o); qb += __shfl_xor_sync(~0u, qb, o);
      }
      const int p0 = r0 >> 1, p1 = 4 + (r0 >> 1);
      const float sA0 = __shfl_sync(~0u, sa, p0), sB0 = __shfl_sync(~0u, sb2, p0);
      const float qA0 = __shfl_sync(~0u, qa, p0), qB0 = __shfl_sync(~0u, qb, p0);
      const float sA1 = __shfl_sync(~0u, sa, p1), sB1 = __shfl_sync(~0u, sb2, p1);
      const float qA1 = __shfl_sync(~0u, qa, p1), qB1 = __shfl_sync(~0u, qb, p1);
      const float invL = 1.0f / (float)L_;
      const float m0 = ((r0 & 1) ? sB0 : sA0) * invL, m1 = ((r0 & 1) ? sB1 : sA1) * invL;
      const float v0 = fmaxf(((r0 & 1) ? qB0 : qA0) * invL - m0 * m0, 0.f);
      const float v1 = fmaxf(((r0 & 1) ? qB1 : qA1) * invL - m1 * m1, 0.f);
      const float rs0 = rsqrtf(v0 + 1e-5f), rs1 = rsqrtf(v1 + 1e-5f);
      const float g0 = __uint_as_float((uint32_t)g0r << 16), g1 = __uint_as_float((uint32_t)g1r << 16);
      const float be0 = __uint_as_float((uint32_t)b0r << 16), be1 = __uint_as_float((uint32_t)b1r << 16);
      sc0 = 0.5f * rs0 * g0; sh0 = 0.5f * be0 - m0 * sc0;
      sc1 = 0.5f * rs1 * g1; sh1 = 0.5f * be1 - m1 * sc1;
      STAMP(4);

      asm volatile("bar.sync %0, 128;" ::"r"(1 + wg) : "memory");
      const int mrow = lane & 7, mi = lane >> 3;
      const uint32_t chunk = (uint32_t)(2 * wq + (mi & 1));
      const uint32_t lane_off = (uint32_t)(((mi >> 1) * 8 + mrow) * 128) + ((chunk ^ (uint32_t)mrow) << 4);
#pragma unroll
      for (int q = 0; q < 4; q++) {
        const uint32_t stage = sb + (q / 3) * SET_BYTES + OFF_W + (q % 3) * W_BYTES + wg * 8192;
        constexpr int NG_FULL = 8;
        const int ng = (q == 3) ? (NT / 8 - 24) : NG_FULL;
#pragma unroll
        for (int ii = 0; ii < NG_FULL; ii += 2) {
          if (ii < ng) {
            const int i = q * 8 + ii;
            const uint32_t a0 = pack_bf16(gelu_half(fmaf(acc[4 * i], sc0, sh0)), gelu_half(fmaf(acc[4 * i + 1], sc0, sh0)));
            const uint32_t a1 = pack_bf16(gelu_half(fmaf(acc[4 * i + 2], sc1, sh1)), gelu_half(fmaf(acc[4 * i + 3], sc1, sh1)));
            if (ii + 1 < ng) {
              const int i2 = (i + 1 < NT / 8) ? i + 1 : i;
              const uint32_t a2 = pack_bf16(gelu_half(fmaf(acc[4 * i2], sc0, sh0)), gelu_half(fmaf(acc[4 * i2 + 1], sc0, sh0)));
              const uint32_t a3 = pack_bf16(gelu_half(fmaf(acc[4 * i2 + 2], sc1, sh1)), gelu_half(fmaf(acc[4 * i2 + 3], sc1, sh1)));
              asm volatile("stmatrix.sync.aligned.m8n8.x4.trans.shared.b16 [%0], {%1, %2, %3, %4};"
                           ::"r"(stage + ii * 1024 + lane_off), "r"(a0), "r"(a1), "r"(a2), "r"(a3) : "memory");
            } else {
              asm volatile("stmatrix.sync.aligned.m8n8.x2.trans.shared.b16 [%0], {%1, %2};"
                           ::"r"(stage + ii * 1024 + lane_off), "r"(a0), "r"(a1) : "memory");
            }
          }
        }
        asm volatile("fence.proxy.async.shared::cta;" ::: "memory");
        __syncwarp();
        if (lane == 0) mbar_arrive_local(bar + 96 + 8 * (wg * 4 + q));
      }
      STAMP(5);
    }
    asm volatile("barrier.cluster.wait.aligned;" ::: "memory");
    STAMP(7);
    if (elected) STAMP_FLUSH(20 * wg);
  }
}

typedef CUresult (*EncodeFn)(CUtensorMap*, CUtensorMapDataType, cuuint32_t, void*, const cuuint64_t*, const cuuint64_t*,
                             const cuuint32_t*, const cuuint32_t*, CUtensorMapInterleave, CUtensorMapSwizzle,
                             CUtensorMapL2promotion, CUtensorMapFloatOOBfill);

}

extern "C" void kernel_launch(void* const* d_in, const int* in_sizes, int n_in, void* d_out, int out_size) {
  (void)in_sizes; (void)n_in; (void)out_size;
  static EncodeFn encode = nullptr;
  static int fused = 0;
  static CUtensorMap mx, mw, mo64, mo56;
  static void* cached[3] = {nullptr, nullptr, nullptr};
  cudaLaunchConfig_t cfg = {};
  cudaLaunchAttribute attr[1];
  cfg.gridDim = dim3(NCTA); cfg.blockDim = dim3(NTHREADS); cfg.dynamicSmemBytes = SMEM_BYTES;
  cfg.stream = cudaStreamPerThread;
  attr[0].id = cudaLaunchAttributeClusterDimension;
  attr[0].val.clusterDim.x = 2; attr[0].val.clusterDim.y = 1; attr[0].val.clusterDim.z = 1;
  cfg.attrs = attr; cfg.numAttrs = 1;
  if (!encode) {
    void* fn = nullptr;
    cudaDriverEntryPointQueryResult qr;
    cudaGetDriverEntryPoint("cuTensorMapEncodeTiled", &fn, cudaEnableDefault, &qr);
    encode = (EncodeFn)fn;
    cudaFuncSetAttribute(conv_stem_kernel, cudaFuncAttributeMaxDynamicSharedMemorySize, SMEM_BYTES);
    int ncl = 0;
    cudaError_t e = cudaOccupancyMaxActiveClusters(&ncl, conv_stem_kernel, &cfg);
    fused = (e == cudaSuccess && ncl >= NCTA / 2 && !FORCE_SPLIT) ? 1 : 0;
    (void)cudaGetLastError();
  }
  if (cached[0] != d_in[0] || cached[1] != d_in[1] || cached[2] != d_out) {
    cached[0] = d_in[0]; cached[1] = d_in[1]; cached[2] = d_out;
    {
      cuuint64_t dims[4] = {D_, 2, T_ / 2, B_};
      cuuint64_t str[3] = {D_ * 2, D_ * 4, (cuuint64_t)T_ * D_ * 2};
      cuuint32_t box[4] = {64, 1, 128, 1}, es[4] = {1, 1, 1, 1};
      encode(&mx, CU_TENSOR_MAP_DATA_TYPE_BFLOAT16, 4, d_in[0], dims, str, box, es, CU_TENSOR_MAP_INTERLEAVE_NONE,
             CU_TENSOR_MAP_SWIZZLE_128B, CU_TENSOR_MAP_L2_PROMOTION_NONE, CU_TENSOR_MAP_FLOAT_OOB_FILL_NONE);
    }
    {
      cuuint64_t dims[2] = {D_, 3 * D_};
      cuuint64_t str[1] = {D_ * 2};
      cuuint32_t box[2] = {64, 64}, es[2] = {1, 1};
      encode(&mw, CU_TENSOR_MAP_DATA_TYPE_BFLOAT16, 2, d_in[1], dims, str, box, es, CU_TENSOR_MAP_INTERLEAVE_NONE,
             CU_TENSOR_MAP_SWIZZLE_128B, CU_TENSOR_MAP_L2_PROMOTION_L2_256B, CU_TENSOR_MAP_FLOAT_OOB_FILL_NONE);
    }
    for (int v = 0; v < 2; v++) {
      cuuint64_t dims[3] = {D_, L_, B_};
      cuuint64_t str[2] = {D_ * 2, (cuuint64_t)L_ * D_ * 2};
      cuuint32_t box[3] = {64, (cuuint32_t)(v ? NT - 192 : 64), 1}, es[3] = {1, 1, 1};
      encode(v ? &mo56 : &mo64, CU_TENSOR_MAP_DATA_TYPE_BFLOAT16, 3, d_out, dims, str, box, es,
             CU_TENSOR_MAP_INTERLEAVE_NONE, CU_TENSOR_MAP_SWIZZLE_128B, CU_TENSOR_MAP_L2_PROMOTION_NONE,
             CU_TENSOR_MAP_FLOAT_OOB_FILL_NONE);
    }
  }
  const __nv_bfloat16* gamma = (const __nv_bfloat16*)d_in[2];
  const __nv_bfloat16* beta = (const __nv_bfloat16*)d_in[3];
  if (fused) {
    cudaLaunchKernelEx(&cfg, conv_stem_kernel, mx, mw, mo64, mo56, gamma, beta, 0);
  } else {
    cudaLaunchKernelEx(&cfg, conv_stem_kernel, mx, mw, mo64, mo56, gamma, beta, 1);
    cudaLaunchKernelEx(&cfg, conv_stem_kernel, mx, mw, mo64, mo56, gamma, beta, 2);
  }
}
```

```cpp
#include <cuda_runtime.h>
#include <cuda_bf16.h>
#include <cuda.h>
#include <stdint.h>

namespace {

constexpr int B_ = 2, T_ = 16000, D_ = 256, L_ = 7999;
constexpr int NT = 248;
constexpr int TILES = 33;
constexpr int NREG = NT / 2;
constexpr int NCTA = B_ * TILES * 2;
constexpr int NTHREADS = 384;

constexpr int X_BYTES = 256 * 128;
constexpr int W_BYTES = 2 * 64 * 128;
constexpr int SET_BYTES = 2 * X_BYTES + 3 * W_BYTES;
constexpr int OFF_E = 0, OFF_O = X_BYTES, OFF_W = 2 * X_BYTES;
constexpr int OFF_BAR = 2 * SET_BYTES;
constexpr int SMEM_BYTES = OFF_BAR + 256 + 1024;

__device__ unsigned long long g_part[4 * TILES * 128];
#define STAMP(i)
#define STAMP_FLUSH(base)

__device__ __forceinline__ uint32_t smem_u32(const void* p) { return (uint32_t)__cvta_generic_to_shared(p); }
__device__ __forceinline__ void mbar_init(uint32_t bar, uint32_t cnt) {
  asm volatile("mbarrier.init.shared::cta.b64 [%0], %1;" ::"r"(bar), "r"(cnt) : "memory");
}
__device__ __forceinline__ void mbar_expect_tx(uint32_t bar, uint32_t bytes) {
  asm volatile("mbarrier.arrive.expect_tx.shared::cta.b64 _, [%0], %1;" ::"r"(bar), "r"(bytes) : "memory");
}
__device__ __forceinline__ bool mbar_try(uint32_t bar, uint32_t parity) {
  uint32_t ok;
  asm volatile("{\n.reg .pred p;\nmbarrier.try_wait.parity.shared::cta.b64 p, [%1], %2;\nselp.u32 %0, 1, 0, p;\n}"
               : "=r"(ok) : "r"(bar), "r"(parity) : "memory");
  return ok;
}
__device__ __forceinline__ bool mbar_try_cl(uint32_t bar, uint32_t parity) {
  uint32_t ok;
  asm volatile("{\n.reg .pred p;\nmbarrier.try_wait.parity.acquire.cluster.shared::cta.b64 p, [%1], %2;\nselp.u32 %0, 1, 0, p;\n}"
               : "=r"(ok) : "r"(bar), "r"(parity) : "memory");
  return ok;
}
constexpr long long WAIT_LIMIT = 100000000ll;
__device__ __forceinline__ void mbar_wait(uint32_t bar, uint32_t parity) {
  if (mbar_try(bar, parity)) return;
  const long long t0 = clock64();
  while (!mbar_try(bar, parity)) if (clock64() - t0 > WAIT_LIMIT) return;
}
__device__ __forceinline__ void mbar_wait_cl(uint32_t bar, uint32_t parity) {
  if (mbar_try_cl(bar, parity)) return;
  const long long t0 = clock64();
  while (!mbar_try_cl(bar, parity)) if (clock64() - t0 > WAIT_LIMIT) return;
}
__device__ __forceinline__ void mbar_arrive_local(uint32_t bar) {
  asm volatile("mbarrier.arrive.shared::cta.b64 _, [%0];" ::"r"(bar) : "memory");
}
__device__ __forceinline__ void mbar_arrive_cluster(uint32_t bar, uint32_t cta) {
  asm volatile("{\n.reg .b32 r;\nmapa.shared::cluster.u32 r, %0, %1;\n"
               "mbarrier.arrive.shared::cluster.b64 _, [r];\n}" ::"r"(bar), "r"(cta) : "memory");
}
__device__ __forceinline__ void tma_x(uint32_t dst, const CUtensorMap* m, uint32_t bar, int c, int par, int l, int b) {
  asm volatile("cp.async.bulk.tensor.4d.shared::cluster.global.mbarrier::complete_tx::bytes.multicast::cluster "
               "[%0], [%1, {%3, %4, %5, %6}], [%2], %7;"
               ::"r"(dst), "l"(m), "r"(bar), "r"(c), "r"(par), "r"(l), "r"(b), "h"((uint16_t)3) : "memory");
}
__device__ __forceinline__ void tma_w(uint32_t dst, const CUtensorMap* m, uint32_t bar, int d, int row) {
  asm volatile("cp.async.bulk.tensor.2d.shared::cluster.global.mbarrier::complete_tx::bytes "
               "[%0], [%1, {%3, %4}], [%2];"
               ::"r"(dst), "l"(m), "r"(bar), "r"(d), "r"(row) : "memory");
}
__device__ __forceinline__ void tma_store(const CUtensorMap* m, uint32_t src, int d, int l, int b) {
  asm volatile("cp.async.bulk.tensor.3d.global.shared::cta.bulk_group [%0, {%2, %3, %4}], [%1];"
               ::"l"(m), "r"(src), "r"(d), "r"(l), "r"(b) : "memory");
}
__device__ __forceinline__ uint64_t make_desc(uint32_t addr) {
  return (uint64_t)((addr & 0x3FFFF) >> 4) | ((uint64_t)1 << 16) | ((uint64_t)64 << 32) | ((uint64_t)1 << 62);
}
__device__ __forceinline__ void wg_fence() { asm volatile("wgmma.fence.sync.aligned;" ::: "memory"); }
__device__ __forceinline__ void wg_commit() { asm volatile("wgmma.commit_group.sync.aligned;" ::: "memory"); }
template <int N> __device__ __forceinline__ void wg_wait() { asm volatile("wgmma.wait_group.sync.aligned %0;" ::"n"(N) : "memory"); }
__device__ __forceinline__ float tanh_fast(float x) { float y; asm("tanh.approx.f32 %0, %1;" : "=f"(y) : "f"(x)); return y; }
__device__ __forceinline__ uint32_t pack_bf16(float lo, float hi) {
  uint32_t r; asm("cvt.rn.bf16x2.f32 %0, %1, %2;" : "=r"(r) : "f"(hi), "f"(lo)); return r;
}
__device__ __forceinline__ float gelu_half(float hh) {
  const float c1 = 2.0f * 0.7978845608028654f, c3 = 8.0f * 0.7978845608028654f * 0.044715f;
  float u = hh * fmaf(hh * hh, c3, c1);
  return fmaf(hh, tanh_fast(u), hh);
}

#define STAG 6
#define FORCE_SPLIT 0

__device__ __forceinline__ void wgmma_n248(float (&d)[124], uint64_t da, uint64_t db, int scale_d) {
  asm volatile("{\n.reg .pred p;\nsetp.ne.b32 p, %126, 0;\n"
    "wgmma.mma_async.sync.aligned.m64n248k16.f32.bf16.bf16 "
    "{%0, %1, %2, %3, %4, %5, %6, %7, %8, %9, %10, %11, %12, %13, %14, %15, "
    "%16, %17, %18, %19, %20, %21, %22, %23, %24, %25, %26, %27, %28, %29, %30, %31, "
    "%32, %33, %34, %35, %36, %37, %38, %39, %40, %41, %42, %43, %44, %45, %46, %47, "
    "%48, %49, %50, %51, %52, %53, %54, %55, %56, %57, %58, %59, %60, %61, %62, %63, "
    "%64, %65, %66, %67, %68, %69, %70, %71, %72, %73, %74, %75, %76, %77, %78, %79, "
    "%80, %81, %82, %83, %84, %85, %86, %87, %88, %89, %90, %91, %92, %93, %94, %95, "
    "%96, %97, %98, %99, %100, %101, %102, %103, %104, %105, %106, %107, %108, %109, %110, %111, "
    "%112, %113, %114, %115, %116, %117, %118, %119, %120, %121, %122, %123}, "
    "%124, %125, p, 1, 1, 1, 0;\n}\n"
    : "+f"(d[0]), "+f"(d[1]), "+f"(d[2]), "+f"(d[3]), "+f"(d[4]), "+f"(d[5]), "+f"(d[6]), "+f"(d[7]),
      "+f"(d[8]), "+f"(d[9]), "+f"(d[10]), "+f"(d[11]), "+f"(d[12]), "+f"(d[13]), "+f"(d[14]), "+f"(d[15]),
      "+f"(d[16]), "+f"(d[17]), "+f"(d[18]), "+f"(d[19]), "+f"(d[20]), "+f"(d[21]), "+f"(d[22]), "+f"(d[23]),
      "+f"(d[24]), "+f"(d[25]), "+f"(d[26]), "+f"(d[27]), "+f"(d[28]), "+f"(d[29]), "+f"(d[30]), "+f"(d[31]),
      "+f"(d[32]), "+f"(d[33]), "+f"(d[34]), "+f"(d[35]), "+f"(d[36]), "+f"(d[37]), "+f"(d[38]), "+f"(d[39]),
      "+f"(d[40]), "+f"(d[41]), "+f"(d[42]), "+f"(d[43]), "+f"(d[44]), "+f"(d[45]), "+f"(d[46]), "+f"(d[47]),
      "+f"(d[48]), "+f"(d[49]), "+f"(d[50]), "+f"(d[51]), "+f"(d[52]), "+f"(d[53]), "+f"(d[54]), "+f"(d[55]),
      "+f"(d[56]), "+f"(d[57]), "+f"(d[58]), "+f"(d[59]), "+f"(d[60]), "+f"(d[61]), "+f"(d[62]), "+f"(d[63]),
      "+f"(d[64]), "+f"(d[65]), "+f"(d[66]), "+f"(d[67]), "+f"(d[68]), "+f"(d[69]), "+f"(d[70]), "+f"(d[71]),
      "+f"(d[72]), "+f"(d[73]), "+f"(d[74]), "+f"(d[75]), "+f"(d[76]), "+f"(d[77]), "+f"(d[78]), "+f"(d[79]),
      "+f"(d[80]), "+f"(d[81]), "+f"(d[82]), "+f"(d[83]), "+f"(d[84]), "+f"(d[85]), "+f"(d[86]), "+f"(d[87]),
      "+f"(d[88]), "+f"(d[89]), "+f"(d[90]), "+f"(d[91]), "+f"(d[92]), "+f"(d[93]), "+f"(d[94]), "+f"(d[95]),
      "+f"(d[96]), "+f"(d[97]), "+f"(d[98]), "+f"(d[99]), "+f"(d[100]), "+f"(d[101]), "+f"(d[102]), "+f"(d[103]),
      "+f"(d[104]), "+f"(d[105]), "+f"(d[106]), "+f"(d[107]), "+f"(d[108]), "+f"(d[109]), "+f"(d[110]), "+f"(d[111]),
      "+f"(d[112]), "+f"(d[113]), "+f"(d[114]), "+f"(d[115]), "+f"(d[116]), "+f"(d[117]), "+f"(d[118]), "+f"(d[119]),
      "+f"(d[120]), "+f"(d[121]), "+f"(d[122]), "+f"(d[123])
    : "l"(da), "l"(db), "r"(scale_d));
}

__global__ void __launch_bounds__(NTHREADS, 1)
conv_stem_kernel(const __grid_constant__ CUtensorMap mx, const __grid_constant__ CUtensorMap mw,
                 const __grid_constant__ CUtensorMap moA, const __grid_constant__ CUtensorMap moB,
                 const __nv_bfloat16* __restrict__ gamma, const __nv_bfloat16* __restrict__ beta, int mode) {
  extern __shared__ uint8_t smem_raw[];
  const uint32_t sb = (smem_u32(smem_raw) + 1023u) & ~1023u;
  const uint32_t bar = sb + OFF_BAR;
  const int tid = threadIdx.x, warp = tid >> 5, lane = tid & 31;
  const int rank = blockIdx.x & 1;
  const int cl = blockIdx.x >> 1;
  const int b = cl / TILES, tile = cl % TILES;
  const int l0 = tile * NT;
  STAMP(0);

  if (tid == 0) {
    asm volatile("prefetch.tensormap [%0];" ::"l"(&mx) : "memory");
    asm volatile("prefetch.tensormap [%0];" ::"l"(&mw) : "memory");
  }
  if (tid == 256) {
    for (int s = 0; s < 2; s++) {
      for (int k = 0; k < 3; k++) mbar_init(bar + 8 * (s * 3 + k), 1);
      mbar_init(bar + 48 + 8 * (s * 3 + 0), 2);
      mbar_init(bar + 48 + 8 * (s * 3 + 1), 4);
      mbar_init(bar + 48 + 8 * (s * 3 + 2), 4);
    }
    for (int k = 0; k < 16; k++) mbar_init(bar + 96 + 8 * k, 4);
    STAMP(14);
    asm volatile("fence.mbarrier_init.release.cluster;" ::: "memory");
    STAMP(15);
  }
  __syncwarp();
  asm volatile("barrier.cluster.arrive.relaxed.aligned;" ::: "memory");
  STAMP(16);
  if (tid == 256) {
    const int dcol = rank * 128;
    mbar_expect_tx(bar, X_BYTES + W_BYTES);
    tma_w(sb + OFF_W, &mw, bar, dcol, 0);
    tma_w(sb + OFF_W + 8192, &mw, bar, dcol + 64, 0);
    mbar_expect_tx(bar + 8, W_BYTES);
    tma_w(sb + OFF_W + W_BYTES, &mw, bar + 8, dcol, 512);
    tma_w(sb + OFF_W + W_BYTES + 8192, &mw, bar + 8, dcol + 64, 512);
  }
  STAMP(17);
  __syncwarp();
  asm volatile("barrier.cluster.wait.acquire.aligned;" ::: "memory");
  STAMP(18);
  if (tid == 256) {
    const int dcol = rank * 128;
    tma_x(sb + OFF_E + rank * (128 * 128), &mx, bar, 0, 0, l0 + rank * 128, b);
    mbar_expect_tx(bar + 16, X_BYTES + W_BYTES);
    tma_x(sb + OFF_O + rank * (128 * 128), &mx, bar + 16, 0, 1, l0 + rank * 128, b);
    tma_w(sb + OFF_W + 2 * W_BYTES, &mw, bar + 16, dcol, 256);
    tma_w(sb + OFF_W + 2 * W_BYTES + 8192, &mw, bar + 16, dcol + 64, 256);
  }
  STAMP(19);

  if (warp >= 8) {
    asm volatile("setmaxnreg.dec.sync.aligned.u32 40;");
    if (tid == 256) {
      const int dcol = rank * 128;
      const uint32_t xoff = rank * (128 * 128);
      const int lr = l0 + rank * 128;
#pragma unroll
      for (int j = 1; j < 4; j++) {
        const int s = j & 1;
        const uint32_t base = sb + s * SET_BYTES;
        const uint32_t fA = bar + 8 * (s * 3), fB = fA + 8, fC = fA + 16;
        const uint32_t eA = fA + 48, eB = fA + 56, eC = fA + 64;
        if (j >= 2) mbar_wait(eA, 0);
        STAMP(1 + 3 * j);
        if (j == 1) mbar_wait(bar, 0);
        mbar_expect_tx(fA, X_BYTES + W_BYTES);
        tma_w(base + OFF_W, &mw, fA, dcol, j * 64);
        tma_w(base + OFF_W + 8192, &mw, fA, dcol + 64, j * 64);
        if (j >= 2) mbar_wait_cl(eB, 0);
        STAMP(2 + 3 * j);
        tma_x(base + OFF_E + xoff, &mx, fA, j * 64, 0, lr, b);
        mbar_expect_tx(fB, W_BYTES);
        tma_w(base + OFF_W + W_BYTES, &mw, fB, dcol, 512 + j * 64);
        tma_w(base + OFF_W + W_BYTES + 8192, &mw, fB, dcol + 64, 512 + j * 64);
        if (j >= 2) mbar_wait_cl(eC, 0);
        STAMP(3 + 3 * j);
        mbar_expect_tx(fC, X_BYTES + W_BYTES);
        tma_x(base + OFF_O + xoff, &mx, fC, j * 64, 1, lr, b);
        tma_w(base + OFF_W + 2 * W_BYTES, &mw, fC, dcol, 256 + j * 64);
        tma_w(base + OFF_W + 2 * W_BYTES + 8192, &mw, fC, dcol + 64, 256 + j * 64);
      }
      STAMP(13);
      STAMP_FLUSH(40);
    }
    if (lane == 0 && warp < 10 && mode != 1) {
      const int wg = warp - 8;
      if (wg == 1) {
        asm volatile("prefetch.tensormap [%0];" ::"l"(&moA) : "memory");
        asm volatile("prefetch.tensormap [%0];" ::"l"(&moB) : "memory");
      }
#pragma unroll
      for (int p = 0; p < 8; p++) {
        mbar_wait(bar + 96 + 8 * (wg * 8 + p), 0);
        if (l0 + p * 32 < L_) {
          const int q = p >> 1;
          const uint32_t stage = sb + (q / 3) * SET_BYTES + OFF_W + (q % 3) * W_BYTES + wg * 8192 + (p & 1) * 4096;
          tma_store(p == 7 ? &moB : &moA, stage, rank * 128 + wg * 64, l0 + p * 32, b);
          asm volatile("cp.async.bulk.commit_group;" ::: "memory");
        }
      }
      asm volatile("cp.async.bulk.wait_group.read 0;" ::: "memory");
    }
    __syncwarp();
    asm volatile("barrier.cluster.arrive.relaxed.aligned;\nbarrier.cluster.wait.aligned;" ::: "memory");
  } else {
    asm volatile("setmaxnreg.inc.sync.aligned.u32 232;");
    const int wg = warp >> 2, wq = warp & 3;
    const int grp = b * 2 + rank;
    const int chw = wg * 64 + wq * 16;
    unsigned long long* part = g_part + (size_t)grp * TILES * 128;
    unsigned long long oldw;
    asm volatile("ld.relaxed.gpu.global.b64 %0, [%1];" : "=l"(oldw) : "l"(part + tile * 128 + chw));
    const int r0 = lane >> 2;
    uint16_t g0r, g1r, b0r, b1r;
    asm volatile("ld.global.nc.b16 %0, [%1];" : "=h"(g0r) : "l"(gamma + rank * 128 + chw + r0));
    asm volatile("ld.global.nc.b16 %0, [%1];" : "=h"(g1r) : "l"(gamma + rank * 128 + chw + r0 + 8));
    asm volatile("ld.global.nc.b16 %0, [%1];" : "=h"(b0r) : "l"(beta + rank * 128 + chw + r0));
    asm volatile("ld.global.nc.b16 %0, [%1];" : "=h"(b1r) : "l"(beta + rank * 128 + chw + r0 + 8));

    STAMP(1);
    float acc[NREG];
    const bool elected = (tid & 127) == 0;
#pragma unroll
    for (int j = 0; j < 4; j++) {
      const int s = j & 1;
      const uint32_t ph = j >> 1;
      const uint32_t base = sb + s * SET_BYTES;
      const uint32_t fA = bar + 8 * (s * 3), fB = fA + 8, fC = fA + 16;
      const uint64_t dE = make_desc(base + OFF_E), dO = make_desc(base + OFF_O);
      const uint64_t dW = make_desc(base + OFF_W + wg * 8192);
      if (3 * j == STAG && wg == 1) {
        if (j == 2) {
          wg_wait<0>();
          if (elected) { uint32_t eC = bar + 48 + 8 * ((s ^ 1) * 3 + 2); mbar_arrive_cluster(eC, 0); mbar_arrive_cluster(eC, 1); }
        }
        asm volatile("bar.sync 3, 256;" ::: "memory");
      }
      mbar_wait(fA, ph);
      STAMP(8 + 3 * j);
      wg_fence();
#pragma unroll
      for (int k = 0; k < 4; k++) wgmma_n248(acc, dW + k * 128, dE + k * 2, (j | k) != 0);
      wg_commit();
      if (j == 1 || (j == 2 && !(STAG == 6 && wg == 1))) {
        wg_wait<1>();
        if (elected) { uint32_t eC = bar + 48 + 8 * ((s ^ 1) * 3 + 2); mbar_arrive_cluster(eC, 0); mbar_arrive_cluster(eC, 1); }
      }
      if (j == 1 && mode != 2 && (lane & 3) < 2) {
        const unsigned long long inv = (unsigned long long)((uint32_t)(oldw >> 32) & 1u) << 32;
        asm volatile("st.relaxed.gpu.global.b64 [%0], %1;" ::"l"(part + tile * 128 + chw + r0 + 8 * (lane & 1)), "l"(inv) : "memory");
      }
      if (3 * j + 1 == STAG && wg == 1) asm volatile("bar.sync 3, 256;" ::: "memory");
      mbar_wait(fB, ph);
      STAMP(9 + 3 * j);
      wg_fence();
#pragma unroll
      for (int k = 0; k < 4; k++) wgmma_n248(acc, dW + (W_BYTES >> 4) + k * 128, dE + 8 + k * 2, 1);
      wg_commit();
      if (j < 2) {
        wg_wait<1>();
        if (elected) mbar_arrive_local(fA + 48);
      }
      if (3 * j + 2 == STAG && wg == 1) asm volatile("bar.sync 3, 256;" ::: "memory");
      mbar_wait(fC, ph);
      STAMP(10 + 3 * j);
      wg_fence();
#pragma unroll
      for (int k = 0; k < 4; k++) wgmma_n248(acc, dW + (2 * W_BYTES >> 4) + k * 128, dO + k * 2, 1);
      wg_commit();
      if (j < 2) {
        wg_wait<1>();
        if (elected) { mbar_arrive_cluster(fB + 48, 0); mbar_arrive_cluster(fB + 48, 1); }
      }
    }
    if (STAG < 12 && wg == 0) asm volatile("bar.arrive 3, 256;" ::: "memory");
    wg_wait<0>();
    STAMP(2);
    asm volatile("barrier.cluster.arrive.relaxed.aligned;" ::: "memory");

    const uint32_t tag = ((uint32_t)(oldw >> 32) & 1u) ^ 1u;
    static_assert(TILES == 33, "partial read pattern assumes 33 tiles");
    constexpr int NI = (TILES + 3) / 4;
    unsigned long long va[NI], vb[NI];
    const uint32_t tagx = tag ^ 1u;
    uint64_t pa = (uint64_t)(part + chw + 2 * (lane & 7) + (lane >> 3) * 128);
    asm volatile("mov.b64 %0, %0;" : "+l"(pa));
    uint32_t pend = (lane < 8) ? ((1u << NI) - 1u) : ((1u << (NI - 1)) - 1u);
#pragma unroll
    for (int i = 0; i < NI; i++) { va[i] = 0; vb[i] = 0; }
    if (mode != 2) {
      float s0 = 0.f, q0 = 0.f, s1 = 0.f, q1 = 0.f;
      static_assert(L_ == T_ / 2 - 1 && (L_ - (TILES - 1) * NT) == 63, "tail handling assumes this geometry");
      if (tile == TILES - 1 && (lane & 3) == 3) { acc[4 * 7 + 1] = 0.f; acc[4 * 7 + 3] = 0.f; }
      {
        float sa[4] = {0.f, 0.f, 0.f, 0.f}, qa[4] = {0.f, 0.f, 0.f, 0.f};
        float sb_[4] = {0.f, 0.f, 0.f, 0.f}, qb[4] = {0.f, 0.f, 0.f, 0.f};
#pragma unroll
        for (int i = 0; i < NT / 8; i++) {
          const int u = (i & 1) * 2;
          sa[u] += acc[4 * i]; sa[u + 1] += acc[4 * i + 1];
          qa[u] = fmaf(acc[4 * i], acc[4 * i], qa[u]); qa[u + 1] = fmaf(acc[4 * i + 1], acc[4 * i + 1], qa[u + 1]);
          sb_[u] += acc[4 * i + 2]; sb_[u + 1] += acc[4 * i + 3];
          qb[u] = fmaf(acc[4 * i + 2], acc[4 * i + 2], qb[u]); qb[u + 1] = fmaf(acc[4 * i + 3], acc[4 * i + 3], qb[u + 1]);
        }
        s0 = (sa[0] + sa[1]) + (sa[2] + sa[3]); q0 = (qa[0] + qa[1]) + (qa[2] + qa[3]);
        s1 = (sb_[0] + sb_[1]) + (sb_[2] + sb_[3]); q1 = (qb[0] + qb[1]) + (qb[2] + qb[3]);
      }
#pragma unroll
      for (int o = 1; o <= 2; o <<= 1) {
        s0 += __shfl_xor_sync(~0u, s0, o); q0 += __shfl_xor_sync(~0u, q0, o);
        s1 += __shfl_xor_sync(~0u, s1, o); q1 += __shfl_xor_sync(~0u, q1, o);
      }
      if ((lane & 3) < 2) {
        const float sv = (lane & 1) ? s1 : s0, qv = (lane & 1) ? q1 : q0;
        const unsigned long long v = (unsigned long long)__float_as_uint(sv) |
                                     ((unsigned long long)((__float_as_uint(qv) & ~1u) | tag) << 32);
        asm volatile("st.relaxed.gpu.global.b64 [%0], %1;" ::"l"(part + tile * 128 + chw + r0 + 8 * (lane & 1)), "l"(v) : "memory");
      }
    }
    STAMP(3);
    float sc0 = 0.f, sh0 = 0.f, sc1 = 0.f, sh1 = 0.f;
    if (mode != 1) {
      const long long tw0 = clock64();
      float sa = 0.f, qa = 0.f, sb2 = 0.f, qb = 0.f;
      while (true) {
#pragma unroll
        for (int i = 0; i < NI; i++)
          if (pend & (1u << i))
            asm volatile("ld.relaxed.gpu.global.v2.b64 {%0, %1}, [%2];" : "=l"(va[i]), "=l"(vb[i]) : "l"(pa + i * 4096) : "memory");
#pragma unroll
        for (int i = 0; i < NI; i++) {
          const uint32_t ta = (uint32_t)(va[i] >> 32) ^ tagx, tb = (uint32_t)(vb[i] >> 32) ^ tagx;
          if ((ta & tb) & 1u) pend &= ~(1u << i);
        }
        if (__all_sync(~0u, pend == 0) || mode == 2 || clock64() - tw0 > WAIT_LIMIT) break;
      }
      STAMP(6);
#pragma unroll
      for (int i = 0; i < NI; i++) {
        const int t = (lane >> 3) + 4 * i;
        if (t < TILES) {
          sa += __uint_as_float((uint32_t)va[i]); qa += __uint_as_float((uint32_t)(va[i] >> 32));
          sb2 += __uint_as_float((uint32_t)vb[i]); qb += __uint_as_float((uint32_t)(vb[i] >> 32));
        }
      }
#pragma unroll
      for (int o = 8; o <= 16; o <<= 1) {
        sa += __shfl_xor_sync(~0u, sa, o); qa += __shfl_xor_sync(~0u, qa, o);
        sb2 += __shfl_xor_sync(~0u, sb2, o); qb += __shfl_xor_sync(~0u, qb, o);
      }
      const int p0 = r0 >> 1, p1 = 4 + (r0 >> 1);
      const float sA0 = __shfl_sync(~0u, sa, p0), sB0 = __shfl_sync(~0u, sb2, p0);
      const float qA0 = __shfl_sync(~0u, qa, p0), qB0 = __shfl_sync(~0u, qb, p0);
      const float sA1 = __shfl_sync(~0u, sa, p1), sB1 = __shfl_sync(~0u, sb2, p1);
      const float qA1 = __shfl_sync(~0u, qa, p1), qB1 = __shfl_sync(~0u, qb, p1);
      const float invL = 1.0f / (float)L_;
      const float m0 = ((r0 & 1) ? sB0 : sA0) * invL, m1 = ((r0 & 1) ? sB1 : sA1) * invL;
      const float v0 = fmaxf(((r0 & 1) ? qB0 : qA0) * invL - m0 * m0, 0.f);
      const float v1 = fmaxf(((r0 & 1) ? qB1 : qA1) * invL - m1 * m1, 0.f);
      const float rs0 = rsqrtf(v0 + 1e-5f), rs1 = rsqrtf(v1 + 1e-5f);
      const float g0 = __uint_as_float((uint32_t)g0r << 16), g1 = __uint_as_float((uint32_t)g1r << 16);
      const float be0 = __uint_as_float((uint32_t)b0r << 16), be1 = __uint_as_float((uint32_t)b1r << 16);
      sc0 = 0.5f * rs0 * g0; sh0 = 0.5f * be0 - m0 * sc0;
      sc1 = 0.5f * rs1 * g1; sh1 = 0.5f * be1 - m1 * sc1;
      STAMP(4);

      asm volatile("bar.sync %0, 128;" ::"r"(1 + wg) : "memory");
      const int mrow = lane & 7, mi = lane >> 3;
      const uint32_t chunk = (uint32_t)(2 * wq + (mi & 1));
      const uint32_t lane_off = (uint32_t)(((mi >> 1) * 8 + mrow) * 128) + ((chunk ^ (uint32_t)mrow) << 4);
#pragma unroll
      for (int q = 0; q < 4; q++) {
        const uint32_t stage = sb + (q / 3) * SET_BYTES + OFF_W + (q % 3) * W_BYTES + wg * 8192;
        constexpr int NG_FULL = 8;
        const int ng = (q == 3) ? (NT / 8 - 24) : NG_FULL;
#pragma unroll
        for (int ii = 0; ii < NG_FULL; ii += 2) {
          if (ii < ng) {
            const int i = q * 8 + ii;
            const uint32_t a0 = pack_bf16(gelu_half(fmaf(acc[4 * i], sc0, sh0)), gelu_half(fmaf(acc[4 * i + 1], sc0, sh0)));
            const uint32_t a1 = pack_bf16(gelu_half(fmaf(acc[4 * i + 2], sc1, sh1)), gelu_half(fmaf(acc[4 * i + 3], sc1, sh1)));
            if (ii + 1 < ng) {
              const int i2 = (i + 1 < NT / 8) ? i + 1 : i;
              const uint32_t a2 = pack_bf16(gelu_half(fmaf(acc[4 * i2], sc0, sh0)), gelu_half(fmaf(acc[4 * i2 + 1], sc0, sh0)));
              const uint32_t a3 = pack_bf16(gelu_half(fmaf(acc[4 * i2 + 2], sc1, sh1)), gelu_half(fmaf(acc[4 * i2 + 3], sc1, sh1)));
              asm volatile("stmatrix.sync.aligned.m8n8.x4.trans.shared.b16 [%0], {%1, %2, %3, %4};"
                           ::"r"(stage + ii * 1024 + lane_off), "r"(a0), "r"(a1), "r"(a2), "r"(a3) : "memory");
            } else {
              asm volatile("stmatrix.sync.aligned.m8n8.x2.trans.shared.b16 [%0], {%1, %2};"
                           ::"r"(stage + ii * 1024 + lane_off), "r"(a0), "r"(a1) : "memory");
            }
          }
          if (ii == 2 || ii == 6) {
            asm volatile("fence.proxy.async.shared::cta;" ::: "memory");
            __syncwarp();
            if (lane == 0) mbar_arrive_local(bar + 96 + 8 * (wg * 8 + 2 * q + (ii >> 2)));
          }
        }
      }
      STAMP(5);
    }
    asm volatile("barrier.cluster.wait.aligned;" ::: "memory");
    STAMP(7);
    if (elected) STAMP_FLUSH(20 * wg);
  }
}

typedef CUresult (*EncodeFn)(CUtensorMap*, CUtensorMapDataType, cuuint32_t, void*, const cuuint64_t*, const cuuint64_t*,
                             const cuuint32_t*, const cuuint32_t*, CUtensorMapInterleave, CUtensorMapSwizzle,
                             CUtensorMapL2promotion, CUtensorMapFloatOOBfill);

}

extern "C" void kernel_launch(void* const* d_in, const int* in_sizes, int n_in, void* d_out, int out_size) {
  (void)in_sizes; (void)n_in; (void)out_size;
  static EncodeFn encode = nullptr;
  static int fused = 0;
  static CUtensorMap mx, mw, moA, moB;
  static void* cached[3] = {nullptr, nullptr, nullptr};
  cudaLaunchConfig_t cfg = {};
  cudaLaunchAttribute attr[1];
  cfg.gridDim = dim3(NCTA); cfg.blockDim = dim3(NTHREADS); cfg.dynamicSmemBytes = SMEM_BYTES;
  cfg.stream = cudaStreamPerThread;
  attr[0].id = cudaLaunchAttributeClusterDimension;
  attr[0].val.clusterDim.x = 2; attr[0].val.clusterDim.y = 1; attr[0].val.clusterDim.z = 1;
  cfg.attrs = attr; cfg.numAttrs = 1;
  if (!encode) {
    void* fn = nullptr;
    cudaDriverEntryPointQueryResult qr;
    cudaGetDriverEntryPoint("cuTensorMapEncodeTiled", &fn, cudaEnableDefault, &qr);
    encode = (EncodeFn)fn;
    cudaFuncSetAttribute(conv_stem_kernel, cudaFuncAttributeMaxDynamicSharedMemorySize, SMEM_BYTES);
    int ncl = 0;
    cudaError_t e = cudaOccupancyMaxActiveClusters(&ncl, conv_stem_kernel, &cfg);
    fused = (e == cudaSuccess && ncl >= NCTA / 2 && !FORCE_SPLIT) ? 1 : 0;
    (void)cudaGetLastError();
  }
  if (cached[0] != d_in[0] || cached[1] != d_in[1] || cached[2] != d_out) {
    cached[0] = d_in[0]; cached[1] = d_in[1]; cached[2] = d_out;
    {
      cuuint64_t dims[4] = {D_, 2, T_ / 2, B_};
      cuuint64_t str[3] = {D_ * 2, D_ * 4, (cuuint64_t)T_ * D_ * 2};
      cuuint32_t box[4] = {64, 1, 128, 1}, es[4] = {1, 1, 1, 1};
      encode(&mx, CU_TENSOR_MAP_DATA_TYPE_BFLOAT16, 4, d_in[0], dims, str, box, es, CU_TENSOR_MAP_INTERLEAVE_NONE,
             CU_TENSOR_MAP_SWIZZLE_128B, CU_TENSOR_MAP_L2_PROMOTION_NONE, CU_TENSOR_MAP_FLOAT_OOB_FILL_NONE);
    }
    {
      cuuint64_t dims[2] = {D_, 3 * D_};
      cuuint64_t str[1] = {D_ * 2};
      cuuint32_t box[2] = {64, 64}, es[2] = {1, 1};
      encode(&mw, CU_TENSOR_MAP_DATA_TYPE_BFLOAT16, 2, d_in[1], dims, str, box, es, CU_TENSOR_MAP_INTERLEAVE_NONE,
             CU_TENSOR_MAP_SWIZZLE_128B, CU_TENSOR_MAP_L2_PROMOTION_L2_256B, CU_TENSOR_MAP_FLOAT_OOB_FILL_NONE);
    }
    for (int v = 0; v < 2; v++) {
      cuuint64_t dims[3] = {D_, L_, B_};
      cuuint64_t str[2] = {D_ * 2, (cuuint64_t)L_ * D_ * 2};
      cuuint32_t box[3] = {64, (cuuint32_t)(v ? NT - 224 : 32), 1}, es[3] = {1, 1, 1};
      encode(v ? &moB : &moA, CU_TENSOR_MAP_DATA_TYPE_BFLOAT16, 3, d_out, dims, str, box, es,
             CU_TENSOR_MAP_INTERLEAVE_NONE, CU_TENSOR_MAP_SWIZZLE_128B, CU_TENSOR_MAP_L2_PROMOTION_NONE,
             CU_TENSOR_MAP_FLOAT_OOB_FILL_NONE);
    }
  }
  const __nv_bfloat16* gamma = (const __nv_bfloat16*)d_in[2];
  const __nv_bfloat16* beta = (const __nv_bfloat16*)d_in[3];
  if (fused) {
    cudaLaunchKernelEx(&cfg, conv_stem_kernel, mx, mw, moA, moB, gamma, beta, 0);
  } else {
    cudaLaunchKernelEx(&cfg, conv_stem_kernel, mx, mw, moA, moB, gamma, beta, 1);
    cudaLaunchKernelEx(&cfg, conv_stem_kernel, mx, mw, moA, moB, gamma, beta, 2);
  }
}
```
